```python
import torch

def _softmax(x, axis=-1):
    return torch.softmax(x, dim=axis)
def _gelu(x):
    return torch.nn.functional.gelu(x, approximate="tanh")
def _silu(x):
    return torch.nn.functional.silu(x)
def _sigmoid(x):
    return torch.sigmoid(x)
def _layernorm(x, axis=-1, eps=1e-5):
    m = x.mean(dim=axis, keepdim=True)
    v = x.var(dim=axis, keepdim=True, unbiased=False)
    return (x - m) / torch.sqrt(v + eps)
def _scatter_add(tgt, idx, src, axis=0):
    return tgt.clone().index_add_(axis, idx, src)
def _segment_sum(src, seg, n):
    out = torch.zeros((n,) + src.shape[1:], dtype=src.dtype)
    return out.index_add_(0, seg, src)
def _pad(x, pw):
    flat = tuple(v for pair in reversed(pw) for v in pair)
    return torch.nn.functional.pad(x, flat)

kernel_name = 'gated_mix__sliding_block_cached__glu_gated_reglu__decode'

def setup_inputs():

    _w = (lambda a: (lambda t: t.to(torch.bfloat16) if t.is_floating_point() else t)(torch.as_tensor(a)))
    def _A_setup():
        B, Sq, D = 1, 1, 640
        Hq, Hkv, Sk, Dh = 32, 32, 32768, 192
        assert Hq % Hkv == 0, (Hq, Hkv)
        return {
            "x": _w((lambda *s: torch.randn(*s, dtype=torch.bfloat16) * 0.05)(B, Sq, D)),
            "k_cache": _w((lambda *s: torch.randn(*s, dtype=torch.bfloat16) * 6.4)(B, Hkv, Sk, Dh)),
            "v_cache": _w((lambda *s: torch.randn(*s, dtype=torch.bfloat16) * 0.05)(B, Hkv, Sk, Dh)),
            "wq": _w((lambda *s: torch.randn(*s, dtype=torch.bfloat16) * 6.4)(D, Hq * Dh) * (D ** -0.5)),
            "wo": _w((lambda *s: torch.randn(*s, dtype=torch.bfloat16) * 0.05)(Hq * Dh, D) * ((Hq * Dh) ** -0.5)),
        }
    _A_in = _A_setup()

    def _B_setup():
        B, S, D, F = 1, 1, 640, 1536
        return {
            "x": _w((lambda *s: torch.randn(*s, dtype=torch.bfloat16) * 0.05)(B, S, D)),
            "W_gate": _w((lambda *s: torch.randn(*s, dtype=torch.bfloat16) * 0.4)(D, F) * (2.0 / D) ** 0.5),
            "W_up": _w((lambda *s: torch.randn(*s, dtype=torch.bfloat16) * 0.4)(D, F) * (2.0 / D) ** 0.5),
            "W_down": _w((lambda *s: torch.randn(*s, dtype=torch.bfloat16) * 0.4)(F, D) * (1.0 / F) ** 0.5),
        }
    _B_in = _B_setup()

    return {
        "A_x": _A_in["x"],
        "A_k_cache": _A_in["k_cache"],
        "A_v_cache": _A_in["v_cache"],
        "A_wq": _A_in["wq"],
        "A_wo": _A_in["wo"],
        "B_x": _B_in["x"],
        "B_W_gate": _B_in["W_gate"],
        "B_W_up": _B_in["W_up"],
        "B_W_down": _B_in["W_down"],
        "gate_w": _w((lambda *s: torch.randn(*s, dtype=torch.bfloat16) * 0.1)(640) * 16.0),
    }

def reference(A_x, A_k_cache, A_v_cache, A_wq, A_wo, B_x, B_W_gate, B_W_up, B_W_down, gate_w):
    def _A_ref(x, k_cache, v_cache, wq, wo):
        B, Sq, D = x.shape
        Hq, Dh = 32, 192
        Hkv, Sk = k_cache.shape[1], k_cache.shape[2]
        W = min(4096, max(256, Sk // 4))
        rep = Hq // Hkv
        q = (lambda x, *d: x.permute(*d))((x @ wq).reshape(B, Sq, Hq, Dh), 0, 2, 1, 3)
        k = (lambda x, n, axis: torch.repeat_interleave(x, n, dim=axis))(k_cache[:, :, Sk - W:, :], rep, axis=1)
        v = (lambda x, n, axis: torch.repeat_interleave(x, n, dim=axis))(v_cache[:, :, Sk - W:, :], rep, axis=1)
        scores = torch.einsum("bhqd,bhkd->bhqk", q, k) * (Dh ** -0.5)
        p = _softmax(scores, axis=-1)
        o = torch.einsum("bhqk,bhkd->bhqd", p, v)
        return (lambda x, *d: x.permute(*d))(o, 0, 2, 1, 3).reshape(B, Sq, Hq * Dh) @ wo

    def _B_ref(x, W_gate, W_up, W_down):
        gate = torch.einsum("bsd,df->bsf", x, W_gate)
        up = torch.einsum("bsd,df->bsf", x, W_up)
        gate = gate * (lambda x, dt: x.to(dt))(gate > 0, gate.dtype)
        h = gate * up
        return torch.einsum("bsf,fd->bsd", h, W_down)

    x = A_x
    g = _sigmoid((x * gate_w).sum(-1, keepdims=True))
    a = _A_ref(x, A_k_cache, A_v_cache, A_wq, A_wo)
    b = _B_ref(x, B_W_gate, B_W_up, B_W_down)
    return g * a + (1 - g) * b
```

```cpp
#include <cuda_runtime.h>
#include <cuda_bf16.h>
#include <stdint.h>

namespace {

constexpr int D_MODEL = 640;
constexpr int NHEAD   = 32;
constexpr int DH      = 192;
constexpr int SK      = 32768;
constexpr int WIN     = 4096;
constexpr int FF      = 1536;

constexpr int THREADS = 384;
constexpr int R3      = 128;
constexpr int R2      = 192;
constexpr int NDS     = D_MODEL / R3;
constexpr int NPCOL   = NHEAD * DH + 2 * FF;
constexpr int KT      = WIN / R3;
constexpr int VREC    = 200;
constexpr int NCG     = D_MODEL / 128;
constexpr int NFROW   = NHEAD + FF / R2;

constexpr int N_WQ  = NHEAD * NDS;
constexpr int N_GU  = 2 * (FF / DH) * NDS;
constexpr int N_KV  = 2 * NHEAD * KT;
constexpr int N_WD  = (FF / R2) * NCG;
constexpr int N_WO  = NHEAD * NCG;
constexpr int N_FIN = NCG;
constexpr int GRID  = N_WQ + N_GU + N_KV + N_WD + N_WO + N_FIN;

#define KV_LAG 12
#define MIN_CTAS 2
constexpr int SPIN_LIMIT = 1 << 20;

__device__ uint32_t g_pp[NDS * NPCOL];
__device__ uint32_t g_sc[NHEAD * WIN];
__device__ uint32_t g_vp[NHEAD * KT * VREC];
__device__ uint32_t g_fin[NCG * NFROW * 128];
__device__ uint32_t g_ctr;

struct Params {
    const char* x;
    const char* k;
    const char* v;
    const char* wq;
    const char* wo;
    const char* wg;
    const char* wu;
    const char* wd;
    const __nv_bfloat16* gate_w;
    __nv_bfloat16* out;
};

__device__ __forceinline__ uint4 ldg_stream(const char* p, uint64_t pol) {
    uint4 v;
    asm volatile("ld.global.nc.L1::no_allocate.L2::cache_hint.v4.u32 {%0,%1,%2,%3}, [%4], %5;"
                 : "=r"(v.x), "=r"(v.y), "=r"(v.z), "=r"(v.w) : "l"(p), "l"(pol));
    return v;
}
__device__ __forceinline__ uint32_t ld_rlx(const uint32_t* p) {
    uint32_t v;
    asm volatile("ld.relaxed.gpu.global.u32 %0, [%1];" : "=r"(v) : "l"(p) : "memory");
    return v;
}
__device__ __forceinline__ uint2 ld_rlx2(const uint32_t* p) {
    uint2 v;
    asm volatile("ld.relaxed.gpu.global.v2.u32 {%0,%1}, [%2];" : "=r"(v.x), "=r"(v.y) : "l"(p) : "memory");
    return v;
}
__device__ __forceinline__ uint4 ld_rlx4(const uint32_t* p) {
    uint4 v;
    asm volatile("ld.relaxed.gpu.global.v4.u32 {%0,%1,%2,%3}, [%4];"
                 : "=r"(v.x), "=r"(v.y), "=r"(v.z), "=r"(v.w) : "l"(p) : "memory");
    return v;
}
__device__ __forceinline__ void st_tag(uint32_t* p, float val, uint32_t tag) {
    uint32_t w = (__float_as_uint(val) & ~1u) | tag;
    asm volatile("st.relaxed.gpu.global.u32 [%0], %1;" :: "l"(p), "r"(w) : "memory");
}
__device__ __forceinline__ float bf_lo(uint32_t w) { return __uint_as_float(w << 16); }
__device__ __forceinline__ float bf_hi(uint32_t w) { return __uint_as_float(w & 0xffff0000u); }
__device__ __forceinline__ float rbf(float x) { return __bfloat162float(__float2bfloat16_rn(x)); }
__device__ __forceinline__ float untag(uint32_t w) { return __uint_as_float(w & ~1u); }
__device__ __forceinline__ float ex2(float x) {
    float y;
    asm("ex2.approx.ftz.f32 %0, %1;" : "=f"(y) : "f"(x));
    return y;
}
constexpr float LOG2E = 1.4426950408889634f;

__device__ __forceinline__ float2 gemv_warp(const uint4 (&d)[8], const float (&w)[8], int lane) {
    float a[8];
#pragma unroll
    for (int j = 0; j < 8; j++) a[j] = 0.f;
#pragma unroll
    for (int p = 0; p < 8; p++) {
        a[0] = fmaf(w[p], bf_lo(d[p].x), a[0]);
        a[1] = fmaf(w[p], bf_hi(d[p].x), a[1]);
        a[2] = fmaf(w[p], bf_lo(d[p].y), a[2]);
        a[3] = fmaf(w[p], bf_hi(d[p].y), a[3]);
        a[4] = fmaf(w[p], bf_lo(d[p].z), a[4]);
        a[5] = fmaf(w[p], bf_hi(d[p].z), a[5]);
        a[6] = fmaf(w[p], bf_lo(d[p].w), a[6]);
        a[7] = fmaf(w[p], bf_hi(d[p].w), a[7]);
    }
    const bool hi16 = lane & 16, hi8 = lane & 8;
    float e[4];
#pragma unroll
    for (int j = 0; j < 4; j++) {
        float keep = hi16 ? a[j + 4] : a[j];
        float send = hi16 ? a[j] : a[j + 4];
        e[j] = keep + __shfl_xor_sync(0xffffffffu, send, 16);
    }
    float2 r;
    {
        float keep = hi8 ? e[2] : e[0], send = hi8 ? e[0] : e[2];
        r.x = keep + __shfl_xor_sync(0xffffffffu, send, 8);
        keep = hi8 ? e[3] : e[1]; send = hi8 ? e[1] : e[3];
        r.y = keep + __shfl_xor_sync(0xffffffffu, send, 8);
    }
    return r;
}

__global__ void __launch_bounds__(THREADS, MIN_CTAS)
fused_decode_kernel(const Params P) {
    __shared__ __align__(16) float s_red[8 * DH];
    __shared__ __align__(16) float s_w[DH];
    __shared__ float s_misc[16];

    const int tid = threadIdx.x, warp = tid >> 5, lane = tid & 31;
    const int g = lane >> 3, c = lane & 7;
    int b = blockIdx.x;

    enum { PROJ, KTILE, VTILE, OUTP, FIN };
    int kind, i0, i1;
    const char* base = nullptr;
    int stride = 0;
    if (b < N_WQ + N_GU) {
        kind = PROJ;
        i0 = b / NDS;
        i1 = b - i0 * NDS;
        if (i0 < NHEAD) { stride = NHEAD * DH * 2; base = P.wq + i0 * (DH * 2); }
        else {
            stride = FF * 2;
            base = (i0 < NHEAD + FF / DH) ? P.wg + (i0 - NHEAD) * (DH * 2) : P.wu + (i0 - NHEAD - FF / DH) * (DH * 2);
        }
        base += (size_t)(i1 * R3) * stride;
    } else if ((b -= N_WQ + N_GU) < N_KV) {
        const int seg = b / KT;
        i1 = b % KT;
        bool isv;
        if (seg < KV_LAG) { isv = false; i0 = seg; }
        else if (seg < 2 * NHEAD - KV_LAG) {
            const int u = seg - KV_LAG;
            isv = !(u & 1);
            i0 = isv ? (u >> 1) : (KV_LAG + (u >> 1));
        } else { isv = true; i0 = seg - NHEAD; }
        kind = isv ? VTILE : KTILE;
        stride = DH * 2;
        base = (isv ? P.v : P.k) + ((size_t)i0 * SK + (SK - WIN) + i1 * R3) * (DH * 2);
    } else if ((b -= N_KV) < N_WD + N_WO) {
        kind = OUTP;
        int rb = b / NCG;
        i1 = b - rb * NCG;
        stride = D_MODEL * 2;
        if (rb < FF / R2) { base = P.wd + (size_t)(rb * R2) * stride; i0 = NHEAD + rb; }
        else { rb -= FF / R2; base = P.wo + (size_t)(rb * R2) * stride; i0 = rb; }
        base += i1 * 256;
    } else {
        kind = FIN; i0 = 0; i1 = b - (N_WD + N_WO);
    }

    int cb, wr;
    if (kind == OUTP) { cb = warp & 1; wr = warp >> 1; }
    else { wr = warp / 3; cb = warp - wr * 3; }
    const int row0 = (wr * 4 + g) * 8;
    uint4 d[8];
    if (kind != FIN) {
        uint64_t pol;
        asm("createpolicy.fractional.L2::evict_first.b64 %0, 1.0;" : "=l"(pol));
        const char* p = base + (size_t)row0 * stride + cb * 128 + c * 16;
#pragma unroll
        for (int j = 0; j < 8; j++) d[j] = ldg_stream(p + (size_t)j * stride, pol);
    }
    const uint32_t tag = (ld_rlx(&g_ctr) >= N_FIN) ? 0u : 1u;

    if (kind == PROJ) {
        const uint4 xv = *reinterpret_cast<const uint4*>(P.x + (i1 * R3 + row0) * 2);
        float w[8] = {bf_lo(xv.x), bf_hi(xv.x), bf_lo(xv.y), bf_hi(xv.y), bf_lo(xv.z), bf_hi(xv.z), bf_lo(xv.w), bf_hi(xv.w)};
        const float2 r = gemv_warp(d, w, lane);
        *reinterpret_cast<float2*>(&s_red[wr * DH + cb * 64 + c * 8 + g * 2]) = r;
        __syncthreads();
        if (tid < DH) {
            const float s = (s_red[tid] + s_red[DH + tid]) + (s_red[2 * DH + tid] + s_red[3 * DH + tid]);
            st_tag(&g_pp[i1 * NPCOL + i0 * DH + tid], s, tag);
        }
    } else if (kind == KTILE) {
        if (tid < DH) {
            const uint32_t* src = &g_pp[i0 * DH + tid];
            uint32_t t[NDS];
            for (int it = 0; it < SPIN_LIMIT; it++) {
                uint32_t bad = 0;
#pragma unroll
                for (int j = 0; j < NDS; j++) { t[j] = ld_rlx(src + j * NPCOL); bad |= t[j] ^ tag; }
                if (!(bad & 1)) break;
                __nanosleep(100);
            }
            float s = 0.f;
#pragma unroll
            for (int j = 0; j < NDS; j++) s += untag(t[j]);
            s_w[tid] = rbf(s);
        }
        __syncthreads();
        const float4 q0 = *reinterpret_cast<const float4*>(&s_w[cb * 64 + c * 8]);
        const float4 q1 = *reinterpret_cast<const float4*>(&s_w[cb * 64 + c * 8 + 4]);
        float a[8];
#pragma unroll
        for (int p = 0; p < 8; p++) {
            float s0 = q0.x * bf_lo(d[p].x);
            float s1 = q0.y * bf_hi(d[p].x);
            s0 = fmaf(q0.z, bf_lo(d[p].y), s0);
            s1 = fmaf(q0.w, bf_hi(d[p].y), s1);
            s0 = fmaf(q1.x, bf_lo(d[p].z), s0);
            s1 = fmaf(q1.y, bf_hi(d[p].z), s1);
            s0 = fmaf(q1.z, bf_lo(d[p].w), s0);
            s1 = fmaf(q1.w, bf_hi(d[p].w), s1);
            a[p] = s0 + s1;
        }
        const bool h4 = c & 4, h2 = c & 2, h1 = c & 1;
        float e[4];
#pragma unroll
        for (int j = 0; j < 4; j++) {
            float keep = h4 ? a[j + 4] : a[j];
            float send = h4 ? a[j] : a[j + 4];
            e[j] = keep + __shfl_xor_sync(0xffffffffu, send, 4);
        }
        float f0, f1;
        {
            float keep = h2 ? e[2] : e[0], send = h2 ? e[0] : e[2];
            f0 = keep + __shfl_xor_sync(0xffffffffu, send, 2);
            keep = h2 ? e[3] : e[1]; send = h2 ? e[1] : e[3];
            f1 = keep + __shfl_xor_sync(0xffffffffu, send, 2);
        }
        const float r = (h1 ? f1 : f0) + __shfl_xor_sync(0xffffffffu, h1 ? f0 : f1, 1);
        s_red[cb * R3 + wr * 32 + lane] = r;
        __syncthreads();
        if (tid < R3) {
            const float s = s_red[tid] + s_red[R3 + tid] + s_red[2 * R3 + tid];
            const float sc = rbf(rbf(s) * 0.07216878364870322f);
            st_tag(&g_sc[i0 * WIN + i1 * R3 + tid], sc, tag);
        }
    } else if (kind == VTILE) {
        float s = 0.f;
        if (tid < R3) {
            const uint32_t* src = &g_sc[i0 * WIN + i1 * R3 + tid];
            uint32_t t;
            for (int it = 0; it < SPIN_LIMIT; it++) {
                t = ld_rlx(src);
                if (!((t ^ tag) & 1)) break;
                __nanosleep(100);
            }
            s = untag(t);
            float m = s;
#pragma unroll
            for (int o = 16; o; o >>= 1) m = fmaxf(m, __shfl_xor_sync(0xffffffffu, m, o));
            if (lane == 0) s_misc[warp] = m;
        }
        __syncthreads();
        const float m = fmaxf(fmaxf(s_misc[0], s_misc[1]), fmaxf(s_misc[2], s_misc[3]));
        if (tid < R3) {
            const float p = ex2((s - m) * LOG2E);
            s_w[tid] = p;
            float l = p;
#pragma unroll
            for (int o = 16; o; o >>= 1) l += __shfl_xor_sync(0xffffffffu, l, o);
            if (lane == 0) s_misc[4 + warp] = l;
        }
        __syncthreads();
        const float4 w0 = *reinterpret_cast<const float4*>(&s_w[row0]);
        const float4 w1 = *reinterpret_cast<const float4*>(&s_w[row0 + 4]);
        float w[8] = {w0.x, w0.y, w0.z, w0.w, w1.x, w1.y, w1.z, w1.w};
        const float2 r = gemv_warp(d, w, lane);
        *reinterpret_cast<float2*>(&s_red[wr * DH + cb * 64 + c * 8 + g * 2]) = r;
        __syncthreads();
        if (tid < VREC) {
            float val;
            if (tid < DH) val = (s_red[tid] + s_red[DH + tid]) + (s_red[2 * DH + tid] + s_red[3 * DH + tid]);
            else if (tid == DH) val = m;
            else val = (s_misc[4] + s_misc[5]) + (s_misc[6] + s_misc[7]);
            st_tag(&g_vp[(i0 * KT + i1) * VREC + tid], val, tag);
        }
    } else if (kind == OUTP) {
        if (i0 < NHEAD) {
            const uint32_t* rec = &g_vp[i0 * KT * VREC];
            const int pg = tid / 48, c4 = tid - pg * 48;
            const uint32_t* src = rec + (pg * 4) * VREC + c4 * 4;
            uint4 t[4];
            uint2 ml;
            for (int it = 0; it < SPIN_LIMIT; it++) {
                ml = ld_rlx2(rec + lane * VREC + DH);
                uint32_t bad = (ml.x ^ tag) | (ml.y ^ tag);
#pragma unroll
                for (int j = 0; j < 4; j++) {
                    t[j] = ld_rlx4(src + j * VREC);
                    bad |= (t[j].x ^ tag) | (t[j].y ^ tag) | (t[j].z ^ tag) | (t[j].w ^ tag);
                }
                if (!(bad & 1)) break;
                __nanosleep(100);
            }
            const float mi = untag(ml.x);
            float M = mi;
#pragma unroll
            for (int o = 16; o; o >>= 1) M = fmaxf(M, __shfl_xor_sync(0xffffffffu, M, o));
            const float f = ex2((mi - M) * LOG2E);
            float L = f * untag(ml.y);
#pragma unroll
            for (int o = 16; o; o >>= 1) L += __shfl_xor_sync(0xffffffffu, L, o);
            float4 o4 = make_float4(0.f, 0.f, 0.f, 0.f);
#pragma unroll
            for (int j = 0; j < 4; j++) {
                const float fj = __shfl_sync(0xffffffffu, f, pg * 4 + j);
                o4.x = fmaf(fj, untag(t[j].x), o4.x);
                o4.y = fmaf(fj, untag(t[j].y), o4.y);
                o4.z = fmaf(fj, untag(t[j].z), o4.z);
                o4.w = fmaf(fj, untag(t[j].w), o4.w);
            }
            *reinterpret_cast<float4*>(&s_red[pg * DH + c4 * 4]) = o4;
            __syncthreads();
            if (tid < DH) {
                float s = 0.f;
#pragma unroll
                for (int j = 0; j < 8; j++) s += s_red[j * DH + tid];
                s_w[tid] = rbf(s / L);
            }
        } else if (tid < R2) {
            const uint32_t* src = &g_pp[NHEAD * DH + (i0 - NHEAD) * R2 + tid];
            uint32_t tg[NDS], tu[NDS];
            for (int it = 0; it < SPIN_LIMIT; it++) {
                uint32_t bad = 0;
#pragma unroll
                for (int j = 0; j < NDS; j++) {
                    tg[j] = ld_rlx(src + j * NPCOL);
                    tu[j] = ld_rlx(src + j * NPCOL + FF);
                    bad |= (tg[j] ^ tag) | (tu[j] ^ tag);
                }
                if (!(bad & 1)) break;
                __nanosleep(100);
            }
            float sg = 0.f, su = 0.f;
#pragma unroll
            for (int j = 0; j < NDS; j++) { sg += untag(tg[j]); su += untag(tu[j]); }
            sg = rbf(sg);
            sg = sg * (sg > 0.f ? 1.f : 0.f);
            s_w[tid] = rbf(sg * rbf(su));
        }
        __syncthreads();
        const float4 w0 = *reinterpret_cast<const float4*>(&s_w[row0]);
        const float4 w1 = *reinterpret_cast<const float4*>(&s_w[row0 + 4]);
        float w[8] = {w0.x, w0.y, w0.z, w0.w, w1.x, w1.y, w1.z, w1.w};
        const float2 r = gemv_warp(d, w, lane);
        *reinterpret_cast<float2*>(&s_red[wr * 128 + cb * 64 + c * 8 + g * 2]) = r;
        __syncthreads();
        if (tid < 128) {
            const float s = (s_red[tid] + s_red[128 + tid]) + (s_red[256 + tid] + s_red[384 + tid]) +
                            (s_red[512 + tid] + s_red[640 + tid]);
            st_tag(&g_fin[(i1 * NFROW + i0) * 128 + tid], s, tag);
        }
    } else {
        if (warp < NFROW / 4) {
            const uint32_t* src = &g_fin[(i1 * NFROW + warp * 4) * 128 + lane * 4];
            uint4 t[4];
            for (int it = 0; it < SPIN_LIMIT; it++) {
                uint32_t bad = 0;
#pragma unroll
                for (int j = 0; j < 4; j++) {
                    t[j] = ld_rlx4(src + j * 128);
                    bad |= (t[j].x ^ tag) | (t[j].y ^ tag) | (t[j].z ^ tag) | (t[j].w ^ tag);
                }
                if (!(bad & 1)) break;
            }
            float4 s;
            s.x = (untag(t[0].x) + untag(t[1].x)) + (untag(t[2].x) + untag(t[3].x));
            s.y = (untag(t[0].y) + untag(t[1].y)) + (untag(t[2].y) + untag(t[3].y));
            s.z = (untag(t[0].z) + untag(t[1].z)) + (untag(t[2].z) + untag(t[3].z));
            s.w = (untag(t[0].w) + untag(t[1].w)) + (untag(t[2].w) + untag(t[3].w));
            *reinterpret_cast<float4*>(&s_red[warp * 128 + lane * 4]) = s;
        } else if (warp == NFROW / 4) {
            const __nv_bfloat16* xb = reinterpret_cast<const __nv_bfloat16*>(P.x);
            float s = 0.f;
#pragma unroll
            for (int j = 0; j < D_MODEL / 32; j++)
                s += rbf(__bfloat162float(xb[j * 32 + lane]) * __bfloat162float(P.gate_w[j * 32 + lane]));
#pragma unroll
            for (int o = 16; o; o >>= 1) s += __shfl_xor_sync(0xffffffffu, s, o);
            s = rbf(s);
            if (lane == 0) s_misc[0] = rbf(1.f / (1.f + __expf(-s)));
        }
        __syncthreads();
        if (tid < 128) {
            float a = 0.f;
#pragma unroll
            for (int j = 0; j < NHEAD / 4; j++) a += s_red[j * 128 + tid];
            const float bb = s_red[(NHEAD / 4) * 128 + tid] + s_red[(NHEAD / 4 + 1) * 128 + tid];
            const float gg = s_misc[0];
            const float r = rbf(gg * rbf(a)) + rbf(rbf(1.f - gg) * rbf(bb));
            P.out[i1 * 128 + tid] = __float2bfloat16_rn(r);
        }
        if (tid == 128)
            asm volatile("red.relaxed.gpu.global.inc.u32 [%0], %1;" :: "l"(&g_ctr), "r"(2 * N_FIN - 1) : "memory");
    }
}

}

extern "C" void kernel_launch(void* const* d_in, const int* in_sizes, int n_in, void* d_out, int out_size) {
    (void)in_sizes; (void)n_in; (void)out_size;
    Params P;
    P.x      = (const char*)d_in[0];
    P.k      = (const char*)d_in[1];
    P.v      = (const char*)d_in[2];
    P.wq     = (const char*)d_in[3];
    P.wo     = (const char*)d_in[4];
    P.wg     = (const char*)d_in[6];
    P.wu     = (const char*)d_in[7];
    P.wd     = (const char*)d_in[8];
    P.gate_w = (const __nv_bfloat16*)d_in[9];
    P.out    = (__nv_bfloat16*)d_out;
    fused_decode_kernel<<<GRID, THREADS, 0, cudaStreamPerThread>>>(P);
}
```

```cpp
#include <cuda_runtime.h>
#include <cuda_bf16.h>
#include <stdint.h>

#define PROF(slot)
#define PROFT(slot, t)
#define PROF_SM()

namespace {

constexpr int D_MODEL = 640;
constexpr int NHEAD   = 32;
constexpr int DH      = 192;
constexpr int SK      = 32768;
constexpr int WIN     = 4096;
constexpr int FF      = 1536;

constexpr int DEP_WARPS  = 2;
constexpr int DATA_WARPS = 6;
constexpr int THREADS = (DATA_WARPS + DEP_WARPS) * 32;
constexpr int KROWS   = 64;
constexpr int OROWS   = 192;
constexpr int NDS     = D_MODEL / KROWS;
constexpr int NPCOL   = NHEAD * DH + 2 * FF;
constexpr int KT      = WIN / KROWS;
constexpr int NCB     = D_MODEL / 64;
constexpr int NFROW   = NHEAD + FF / OROWS;

#define S_DIST 6
#define C_DIST 4
#define LATE_HEADS 6
#define EARLY_WO 20
#define MIN_CTAS 2
#define SMEM_PAD 9000
#define CARVEOUT 14
#define STAGGER 14
#define STAG_P0 30
#define FIRST_WAVE 264
#define PC0_POS 350
#define FIN_SEG 4
#define DELAY_C 400
#define DELAY_O 600
#define DELAY_O_HEADS 2
#define BACKOFF 64

constexpr int N_PROJ = (NPCOL / DH) * NDS;
constexpr int N_PRE  = N_PROJ + 2;
constexpr int PCCOL  = 3 * DH;
constexpr int SEG    = KT + 4;
constexpr int SEG_V  = NHEAD;
constexpr int SEG_O  = 2 * NHEAD;
constexpr int N_OUT  = NFROW * NCB;
constexpr int OPART  = N_OUT % KT;
constexpr int NSEG   = SEG_O + N_OUT / KT + 1;
constexpr int SEG_F  = SEG_O + FIN_SEG;
constexpr int N_FIN  = NCB;
constexpr int GRID   = N_PRE + SEG * NSEG;
constexpr int SPIN_LIMIT = 1 << 20;
constexpr uint64_t EVICT_FIRST = 0x12F0000000000000ull;
constexpr int C_LAST = SEG_F - SEG_V - C_DIST;
static_assert(OPART + N_FIN + 3 * (NHEAD - 1 - C_LAST) <= KT, "no room for the late combines");

constexpr int OFF_PP  = 0;
constexpr int OFF_F   = OFF_PP + NDS * NPCOL;
constexpr int OFF_SC  = OFF_F + NPCOL + NHEAD * DH;
constexpr int OFF_ML  = OFF_SC + NHEAD * WIN;
constexpr int OFF_VP  = OFF_ML + NHEAD * 8;
constexpr int OFF_FIN = OFF_VP + NHEAD * KT * DH;
constexpr int OFF_CTR = OFF_FIN + NCB * NFROW * 64;
constexpr int SCRATCH_WORDS = OFF_CTR + 32;
__device__ __align__(256) uint32_t g_scratch[SCRATCH_WORDS];

struct Params {
    const char* wq;
    const char* k;
    const char* v;
    uint32_t* s;
    const char* x;
    const char* wo;
    const char* wg;
    const char* wu;
    const char* wd;
    const __nv_bfloat16* gate_w;
    __nv_bfloat16* out;
};

template <int STRIDE>
__device__ __forceinline__ void load_tile(uint4 (&d)[8], const char* p) {
#pragma unroll
    for (int j = 0; j < 8; j++)
        asm volatile("ld.global.nc.L1::no_allocate.L2::cache_hint.v4.u32 {%0,%1,%2,%3}, [%4], %5;"
                     : "=r"(d[j].x), "=r"(d[j].y), "=r"(d[j].z), "=r"(d[j].w) : "l"(p + j * STRIDE), "l"(EVICT_FIRST));
}
__device__ __forceinline__ uint32_t ld_rlx(const uint32_t* p) {
    uint32_t v;
    asm volatile("ld.relaxed.gpu.global.u32 %0, [%1];" : "=r"(v) : "l"(p) : "memory");
    return v;
}
__device__ __forceinline__ uint2 ld_rlx2(const uint32_t* p) {
    uint2 v;
    asm volatile("ld.relaxed.gpu.global.v2.u32 {%0,%1}, [%2];" : "=r"(v.x), "=r"(v.y) : "l"(p) : "memory");
    return v;
}
__device__ __forceinline__ uint4 ld_rlx4(const uint32_t* p) {
    uint4 v;
    asm volatile("ld.relaxed.gpu.global.v4.u32 {%0,%1,%2,%3}, [%4];"
                 : "=r"(v.x), "=r"(v.y), "=r"(v.z), "=r"(v.w) : "l"(p) : "memory");
    return v;
}
__device__ __forceinline__ bool stale4(const uint4& v, uint32_t tag) {
    return (((v.x ^ tag) | (v.y ^ tag) | (v.z ^ tag) | (v.w ^ tag)) & 1u) != 0;
}
__device__ __forceinline__ void st_tag(uint32_t* p, float val, uint32_t tag) {
    uint32_t w = (__float_as_uint(val) & ~1u) | tag;
    asm volatile("st.relaxed.gpu.global.u32 [%0], %1;" :: "l"(p), "r"(w) : "memory");
}
__device__ __forceinline__ void st_rlx4(uint32_t* p, uint32_t a, uint32_t b, uint32_t c, uint32_t d) {
    asm volatile("st.relaxed.gpu.global.v4.u32 [%0], {%1,%2,%3,%4};" :: "l"(p), "r"(a), "r"(b), "r"(c), "r"(d) : "memory");
}
__device__ __forceinline__ float bf_lo(uint32_t w) { return __uint_as_float(w << 16); }
__device__ __forceinline__ float bf_hi(uint32_t w) { return __uint_as_float(w & 0xffff0000u); }
__device__ __forceinline__ float rbf(float x) { return __bfloat162float(__float2bfloat16_rn(x)); }
__device__ __forceinline__ float untag(uint32_t w) { return __uint_as_float(w & ~1u); }
__device__ __forceinline__ float ex2(float x) {
    float y;
    asm("ex2.approx.ftz.f32 %0, %1;" : "=f"(y) : "f"(x));
    return y;
}
constexpr float LOG2E = 1.4426950408889634f;
__device__ __forceinline__ uint32_t cur_tag(const uint32_t* s) { return (ld_rlx(s + OFF_CTR) >= N_FIN) ? 0u : 1u; }
template <int N>
__device__ __forceinline__ float4 sum_n(const uint4 (&t)[N]) {
    float4 a = make_float4(untag(t[0].x), untag(t[0].y), untag(t[0].z), untag(t[0].w));
    float4 b = make_float4(untag(t[1].x), untag(t[1].y), untag(t[1].z), untag(t[1].w));
#pragma unroll
    for (int j = 2; j < N; j += 2) {
        a.x += untag(t[j].x); a.y += untag(t[j].y); a.z += untag(t[j].z); a.w += untag(t[j].w);
        b.x += untag(t[j + 1].x); b.y += untag(t[j + 1].y); b.z += untag(t[j + 1].z); b.w += untag(t[j + 1].w);
    }
    return make_float4(a.x + b.x, a.y + b.y, a.z + b.z, a.w + b.w);
}
template <int SLEEP, int N>
__device__ __forceinline__ uint32_t fetch_n(uint4 (&t)[N], const uint32_t* s, const uint32_t* src, int stride, int limit) {
#pragma unroll
    for (int j = 0; j < N; j++) t[j] = ld_rlx4(src + j * stride);
    const uint32_t tag = cur_tag(s);
#pragma unroll 1
    for (int it = 0; it < limit; it++) {
        bool st[N], any = false;
#pragma unroll
        for (int j = 0; j < N; j++) { st[j] = stale4(t[j], tag); any |= st[j]; }
        if (!any) break;
        if (SLEEP) __nanosleep(SLEEP);
#pragma unroll
        for (int j = 0; j < N; j++) if (st[j]) t[j] = ld_rlx4(src + j * stride);
    }
    return tag;
}
__device__ __forceinline__ void spin_cycles(int cycles) {
    const uint32_t t0 = clock();
    while ((int)((uint32_t)clock() - t0) < cycles) {}
}
__device__ __forceinline__ void bar_sync(int id, int n) { asm volatile("bar.sync %0, %1;" :: "r"(id), "r"(n) : "memory"); }
__device__ __forceinline__ void bar_arrive(int id, int n) { asm volatile("bar.arrive %0, %1;" :: "r"(id), "r"(n) : "memory"); }

__device__ __forceinline__ void out_tile(int n, int r, int& rb, int& cbk) {
    const int o = (n - SEG_O) * KT + r - (n > SEG_F ? KT - OPART : 0);
    rb = o / NCB;
    cbk = o - rb * NCB;
    if (rb >= EARLY_WO) rb = (rb < EARLY_WO + FF / OROWS) ? rb + (NHEAD - EARLY_WO) : rb - FF / OROWS;
}

__global__ void __launch_bounds__(THREADS, MIN_CTAS)
fused_decode_kernel(const Params P) {
    __shared__ __align__(16) float s_red[16 * 64];
    __shared__ __align__(16) float s_w[DH];
    __shared__ float s_misc[16];
    __shared__ uint32_t s_tag;

    const int tid = threadIdx.x;
    const int b = blockIdx.x;
    PROF(0); PROF_SM();
    const uint32_t bs = (uint32_t)(b + (8 * SEG - N_PRE));
    int n = (int)(bs / SEG), r = (int)(bs - n * SEG);
    n -= 8;
    if (n < 0) r = b - (b >= PC0_POS + 2 ? 2 : 0);
    const bool tile = (n < 0) ? ((uint32_t)(b - PC0_POS) >= 2u) : (r < ((n == SEG_F) ? OPART : KT));

    if (!tile || tid >= DATA_WARPS * 32) {
        const int lane = tid & 31, warp = tid >> 5;
        if (tile) {
            const int dt = tid - DATA_WARPS * 32;
            PROFT(4, DATA_WARPS * 32);
            uint32_t tag = 0;
            if (n < 0) {
                if (dt < 32) {
                    const uint32_t xv = *reinterpret_cast<const uint32_t*>(P.x + ((r % NDS) * KROWS + dt * 2) * 2);
                    tag = cur_tag(P.s);
                    PROFT(5, DATA_WARPS * 32);
                    *reinterpret_cast<float2*>(&s_w[dt * 2]) = make_float2(bf_lo(xv), bf_hi(xv));
                }
            } else if (n >= SEG_V && n < SEG_O) {
                if (dt < 32) {
                    const int h = n - SEG_V;
                    const uint32_t* src = &P.s[OFF_SC + h * WIN + r * KROWS + lane * 2];
                    uint2 t = ld_rlx2(src);
                    uint2 ml = ld_rlx2(&P.s[OFF_ML + h * 8]);
                    tag = cur_tag(P.s);
#pragma unroll 1
                    for (int it = 0; it < SPIN_LIMIT; it++) {
                        if (!(((t.x ^ tag) | (t.y ^ tag) | (ml.x ^ tag) | (ml.y ^ tag)) & 1u)) break;
                        __nanosleep(BACKOFF);
                        t = ld_rlx2(src);
                        ml = ld_rlx2(&P.s[OFF_ML + h * 8]);
                    }
                    PROFT(5, DATA_WARPS * 32);
                    const float m = untag(ml.x), il = untag(ml.y);
                    *reinterpret_cast<float2*>(&s_w[lane * 2]) =
                        make_float2(rbf(ex2((untag(t.x) - m) * LOG2E) * il), rbf(ex2((untag(t.y) - m) * LOG2E) * il));
                }
            } else if (dt < DH / 4) {
                int rb = n, cbk;
                bool ffn = false;
                if (n >= SEG_O) {
                    out_tile(n, r, rb, cbk);
                    ffn = rb >= NHEAD;
                    if (DELAY_O && !ffn && rb >= NHEAD - DELAY_O_HEADS) spin_cycles(DELAY_O);
                    if (!ffn) rb += NPCOL / DH;
                }
                const uint32_t* src = &P.s[OFF_F + rb * DH + dt * 4];
                const uint32_t* src2 = src + (ffn ? FF : 0);
                uint4 t = ld_rlx4(src), u = t;
                if (ffn) u = ld_rlx4(src2);
                tag = cur_tag(P.s);
#pragma unroll 1
                for (int it = 0; it < SPIN_LIMIT && (stale4(t, tag) || stale4(u, tag)); it++) {
                    __nanosleep(BACKOFF);
                    t = ld_rlx4(src);
                    u = ld_rlx4(src2);
                }
                PROFT(5, DATA_WARPS * 32);
                float4 q = make_float4(untag(t.x), untag(t.y), untag(t.z), untag(t.w));
                if (ffn) {
                    q.x = rbf(q.x * (q.x > 0.f ? 1.f : 0.f) * untag(u.x));
                    q.y = rbf(q.y * (q.y > 0.f ? 1.f : 0.f) * untag(u.y));
                    q.z = rbf(q.z * (q.z > 0.f ? 1.f : 0.f) * untag(u.z));
                    q.w = rbf(q.w * (q.w > 0.f ? 1.f : 0.f) * untag(u.w));
                }
                *reinterpret_cast<float4*>(&s_w[dt * 4]) = q;
            }
            if (dt == 0) s_tag = tag;
            __syncwarp();
            PROFT(1, DATA_WARPS * 32);
            bar_arrive(1, THREADS);
            return;
        }

        PROF(4);
        int e = r - KT;
        int h = n - (e < 3 ? SEG_V + C_DIST : S_DIST);
        if (e < 3 && h > C_LAST) h = -1;
        if (n == SEG_F && e < 0) {
            const int k = r - (OPART + N_FIN);
            h = C_LAST + 1 + k / 3;
            e = (k < 0) ? 4 : k % 3;
        }
        if (n < 0 || (e < 2 && n < NPCOL / (2 * PCCOL) - 1)) {
            if (tid < PCCOL / 4) {
                const int col = (n < 0 ? b - PC0_POS : 2 * n + 2 + e) * PCCOL + tid * 4;
                uint4 t[NDS];
                const uint32_t tag = fetch_n<BACKOFF>(t, P.s, &P.s[OFF_PP + col], NPCOL, SPIN_LIMIT);
                PROF(5);
                const float4 v = sum_n(t);
                st_rlx4(&P.s[OFF_F + col], __float_as_uint(rbf(v.x)) | tag, __float_as_uint(rbf(v.y)) | tag,
                        __float_as_uint(rbf(v.z)) | tag, __float_as_uint(rbf(v.w)) | tag);
            }
            PROF(1); PROF(2);
        } else if (e == 4) {
            const int cbk = r - OPART;
            const int rg = tid >> 4, c4 = tid & 15;
            if (warp == 7) {
                const uint32_t* xb = reinterpret_cast<const uint32_t*>(P.x);
                const uint32_t* gb = reinterpret_cast<const uint32_t*>(P.gate_w);
                float s = 0.f;
#pragma unroll
                for (int j = 0; j < D_MODEL / 64; j++) {
                    const uint32_t xv = xb[j * 32 + lane], gv = gb[j * 32 + lane];
                    s += rbf(bf_lo(xv) * bf_lo(gv)) + rbf(bf_hi(xv) * bf_hi(gv));
                }
#pragma unroll
                for (int o = 16; o; o >>= 1) s += __shfl_xor_sync(0xffffffffu, s, o);
                s = rbf(s);
                if (lane == 0) s_misc[0] = rbf(1.f / (1.f + __expf(-s)));
            }
#pragma unroll 1
            for (int pass = 0; pass < 2; pass++) {
                if (rg < NFROW / 4) {
                    uint4 t[4];
                    fetch_n<0>(t, P.s, &P.s[OFF_FIN + (cbk * NFROW + rg * 4) * 64 + c4 * 4], 64, pass ? SPIN_LIMIT : 0);
                    PROF(5);
                    *reinterpret_cast<float4*>(&s_red[rg * 64 + c4 * 4]) = sum_n(t);
                }
                __syncthreads();
                if (tid < 64) {
                    float a = 0.f;
#pragma unroll
                    for (int j = 0; j < NHEAD / 4; j++) a += s_red[j * 64 + tid];
                    const float bb = s_red[(NHEAD / 4) * 64 + tid] + s_red[(NHEAD / 4 + 1) * 64 + tid];
                    const float gg = s_misc[0];
                    const float res = rbf(gg * rbf(a)) + rbf(rbf(1.f - gg) * rbf(bb));
                    const unsigned short rb = __bfloat16_as_ushort(__float2bfloat16_rn(res));
                    asm volatile("{ .reg .pred p; setp.ne.s32 p, %2, 0; @p st.global.u16 [%0], %1; }"
                                 :: "l"(P.out + cbk * 64 + tid), "h"(rb), "r"(pass) : "memory");
                }
                if (pass == 0) __syncthreads();
            }
            if (tid == 64)
                asm volatile("red.relaxed.gpu.global.inc.u32 [%0], %1;" :: "l"(P.s + OFF_CTR), "r"(2 * N_FIN - 1) : "memory");
        } else if (h < 0 || h >= NHEAD) {
            PROF(5); PROF(1); PROF(2);
        } else if (e < 3) {
            const int pg = tid >> 4, c4 = tid & 15;
            uint4 t[4];
            if (DELAY_C) spin_cycles(DELAY_C);
            const uint32_t tag = fetch_n<BACKOFF>(t, P.s, &P.s[OFF_VP + (h * KT + pg * 4) * DH + e * 64 + c4 * 4], DH, SPIN_LIMIT);
            PROF(5);
            float4 acc = sum_n(t);
            acc.x += __shfl_xor_sync(0xffffffffu, acc.x, 16);
            acc.y += __shfl_xor_sync(0xffffffffu, acc.y, 16);
            acc.z += __shfl_xor_sync(0xffffffffu, acc.z, 16);
            acc.w += __shfl_xor_sync(0xffffffffu, acc.w, 16);
            if (lane < 16) *reinterpret_cast<float4*>(&s_red[warp * 64 + c4 * 4]) = acc;
            __syncthreads();
            PROF(1); PROF(2);
            if (tid < 64) {
                float s = 0.f;
#pragma unroll
                for (int j = 0; j < 8; j++) s += s_red[j * 64 + tid];
                st_tag(&P.s[OFF_F + NPCOL + h * DH + e * 64 + tid], rbf(s), tag);
            }
        } else {
            uint4 t[4];
            const uint32_t tag = fetch_n<BACKOFF>(t, P.s, &P.s[OFF_SC + h * WIN + tid * 4], THREADS * 4, SPIN_LIMIT);
            PROF(5);
            if (h >= NHEAD - LATE_HEADS) {
                const uint32_t z = tag ^ 1u;
#pragma unroll
                for (int j = 0; j < KT * DH / (THREADS * 4); j++) st_rlx4(&P.s[OFF_VP + h * KT * DH + (j * THREADS + tid) * 4], z, z, z, z);
                if (tid < DH / 4) st_rlx4(&P.s[OFF_F + NPCOL + h * DH + tid * 4], z, z, z, z);
                __threadfence();
            }
            float m = -INFINITY;
#pragma unroll
            for (int j = 0; j < 4; j++)
                m = fmaxf(fmaxf(m, fmaxf(untag(t[j].x), untag(t[j].y))), fmaxf(untag(t[j].z), untag(t[j].w)));
#pragma unroll
            for (int o = 16; o; o >>= 1) m = fmaxf(m, __shfl_xor_sync(0xffffffffu, m, o));
            if (lane == 0) s_misc[warp] = m;
            __syncthreads();
#pragma unroll
            for (int j = 0; j < 8; j++) m = fmaxf(m, s_misc[j]);
            float l = 0.f;
#pragma unroll
            for (int j = 0; j < 4; j++)
                l += (ex2((untag(t[j].x) - m) * LOG2E) + ex2((untag(t[j].y) - m) * LOG2E)) +
                     (ex2((untag(t[j].z) - m) * LOG2E) + ex2((untag(t[j].w) - m) * LOG2E));
#pragma unroll
            for (int o = 16; o; o >>= 1) l += __shfl_xor_sync(0xffffffffu, l, o);
            if (lane == 0) s_misc[8 + warp] = l;
            __syncthreads();
            PROF(1); PROF(2);
            if (tid < 8) {
                l = 0.f;
#pragma unroll
                for (int j = 0; j < 8; j++) l += s_misc[8 + j];
                st_tag(&P.s[OFF_ML + h * 8 + tid], tid == 0 ? m : 1.f / l, tag);
            }
        }
        PROF(3);
        return;
    }

    const int c = tid & 7, rg = tid >> 3;
    const int wr = tid >= 96;
    const int wrow = wr * 32 + (rg & 3) * 8;
    const int wcol = ((tid >> 5) - wr * 3) * 128 + c * 16;
    uint4 d[8];
    uint32_t* dst;
    if (n >= SEG_O) {
        int rb, cbk;
        out_tile(n, r, rb, cbk);
        const char* w = (rb < NHEAD) ? P.wo : P.wd - NHEAD * OROWS * (D_MODEL * 2);
        load_tile<D_MODEL * 2>(d, w + (uint32_t)((rb * OROWS + rg * 8) * (D_MODEL * 2) + cbk * 128 + c * 16));
        dst = &P.s[OFF_FIN + (cbk * NFROW + rb) * 64 + tid];
    } else if (n >= 0) {
        const bool isv = n >= SEG_V;
        const int h = n & (NHEAD - 1);
        load_tile<DH * 2>(d, (isv ? P.v : P.k) + (size_t)h * (SK * DH * 2) + (uint32_t)((r * KROWS + wrow) * (DH * 2) + wcol));
        dst = isv ? &P.s[OFF_VP + (h * KT + r) * DH + tid] : &P.s[OFF_SC + h * WIN + r * KROWS + tid];
    } else {
        const int cbk = r / NDS, ds = r - cbk * NDS;
        const int row = ds * KROWS + wrow;
        if (STAGGER && b < FIRST_WAVE) {
            spin_cycles((b - STAG_P0) * STAGGER);
        }
        if (cbk >= NHEAD) {
            const char* w = (cbk < NHEAD + FF / DH) ? P.wg - NHEAD * (DH * 2) : P.wu - (NHEAD + FF / DH) * (DH * 2);
            load_tile<FF * 2>(d, w + (uint32_t)(row * (FF * 2) + cbk * (DH * 2) + wcol));
        } else {
            load_tile<NHEAD * DH * 2>(d, P.wq + (uint32_t)(row * (NHEAD * DH * 2) + cbk * (DH * 2) + wcol));
        }
        dst = &P.s[OFF_PP + ds * NPCOL + cbk * DH + tid];
    }
    PROF(7);
    bar_sync(1, THREADS);
    const uint32_t tag = s_tag;
    const int lane = tid & 31, warp = tid >> 5;

    if ((uint32_t)n < (uint32_t)SEG_V) {
        const float4 q0 = *reinterpret_cast<const float4*>(&s_w[wcol >> 1]);
        const float4 q1 = *reinterpret_cast<const float4*>(&s_w[(wcol >> 1) + 4]);
        float a[8];
#pragma unroll
        for (int p = 0; p < 8; p++) {
            float s0 = q0.x * bf_lo(d[p].x);
            float s1 = q0.y * bf_hi(d[p].x);
            s0 = fmaf(q0.z, bf_lo(d[p].y), s0);
            s1 = fmaf(q0.w, bf_hi(d[p].y), s1);
            s0 = fmaf(q1.x, bf_lo(d[p].z), s0);
            s1 = fmaf(q1.y, bf_hi(d[p].z), s1);
            s0 = fmaf(q1.z, bf_lo(d[p].w), s0);
            s1 = fmaf(q1.w, bf_hi(d[p].w), s1);
            a[p] = s0 + s1;
        }
        const bool h4 = c & 4, h2 = c & 2, h1 = c & 1;
        float e[4];
#pragma unroll
        for (int j = 0; j < 4; j++) {
            float keep = h4 ? a[j + 4] : a[j];
            float send = h4 ? a[j] : a[j + 4];
            e[j] = keep + __shfl_xor_sync(0xffffffffu, send, 4);
        }
        float f0, f1;
        {
            float keep = h2 ? e[2] : e[0], send = h2 ? e[0] : e[2];
            f0 = keep + __shfl_xor_sync(0xffffffffu, send, 2);
            keep = h2 ? e[3] : e[1]; send = h2 ? e[1] : e[3];
            f1 = keep + __shfl_xor_sync(0xffffffffu, send, 2);
        }
        const float s = (h1 ? f1 : f0) + __shfl_xor_sync(0xffffffffu, h1 ? f0 : f1, 1);
        s_red[(warp - wr * 3) * KROWS + wr * 32 + lane] = s;
        bar_sync(2, DATA_WARPS * 32);
        PROF(2);
        if (tid < KROWS) {
            const float t = s_red[tid] + s_red[KROWS + tid] + s_red[2 * KROWS + tid];
            st_tag(dst, rbf(rbf(t) * 0.07216878364870322f), tag);
        }
    } else {
        const bool wide = n < SEG_O;
        const int row0 = wide ? wrow : rg * 8;
        const float4 w0 = *reinterpret_cast<const float4*>(&s_w[row0]);
        const float4 w1 = *reinterpret_cast<const float4*>(&s_w[row0 + 4]);
        const float w[8] = {w0.x, w0.y, w0.z, w0.w, w1.x, w1.y, w1.z, w1.w};
        float a[8];
#pragma unroll
        for (int j = 0; j < 8; j++) a[j] = 0.f;
#pragma unroll
        for (int p = 0; p < 8; p++) {
            a[0] = fmaf(w[p], bf_lo(d[p].x), a[0]);
            a[1] = fmaf(w[p], bf_hi(d[p].x), a[1]);
            a[2] = fmaf(w[p], bf_lo(d[p].y), a[2]);
            a[3] = fmaf(w[p], bf_hi(d[p].y), a[3]);
            a[4] = fmaf(w[p], bf_lo(d[p].z), a[4]);
            a[5] = fmaf(w[p], bf_hi(d[p].z), a[5]);
            a[6] = fmaf(w[p], bf_lo(d[p].w), a[6]);
            a[7] = fmaf(w[p], bf_hi(d[p].w), a[7]);
        }
        const bool hi16 = lane & 16, hi8 = lane & 8;
        float e[4];
#pragma unroll
        for (int j = 0; j < 4; j++) {
            float keep = hi16 ? a[j + 4] : a[j];
            float send = hi16 ? a[j] : a[j + 4];
            e[j] = keep + __shfl_xor_sync(0xffffffffu, send, 16);
        }
        float2 o;
        {
            float keep = hi8 ? e[2] : e[0], send = hi8 ? e[0] : e[2];
            o.x = keep + __shfl_xor_sync(0xffffffffu, send, 8);
            keep = hi8 ? e[3] : e[1]; send = hi8 ? e[1] : e[3];
            o.y = keep + __shfl_xor_sync(0xffffffffu, send, 8);
        }
        *reinterpret_cast<float2*>(&s_red[warp * 64 + c * 8 + (rg & 3) * 2]) = o;
        bar_sync(2, DATA_WARPS * 32);
        PROF(2);
        if (wide) {
            st_tag(dst, s_red[tid] + s_red[DH + tid], tag);
        } else if (tid < 64) {
            st_tag(dst, (s_red[tid] + s_red[64 + tid]) + (s_red[128 + tid] + s_red[192 + tid]) +
                        (s_red[256 + tid] + s_red[320 + tid]), tag);
        }
    }
    PROF(3);
}

}

extern "C" void kernel_launch(void* const* d_in, const int* in_sizes, int n_in, void* d_out, int out_size) {
    (void)in_sizes; (void)n_in; (void)out_size;
    Params P;
    P.x      = (const char*)d_in[0];
    P.k      = (const char*)d_in[1] + (size_t)(SK - WIN) * DH * 2;
    P.v      = (const char*)d_in[2] + (size_t)(SK - WIN) * DH * 2;
    P.wq     = (const char*)d_in[3];
    P.wo     = (const char*)d_in[4];
    P.wg     = (const char*)d_in[6];
    P.wu     = (const char*)d_in[7];
    P.wd     = (const char*)d_in[8];
    P.gate_w = (const __nv_bfloat16*)d_in[9];
    P.out    = (__nv_bfloat16*)d_out;
    void* scratch = nullptr;
    cudaGetSymbolAddress(&scratch, g_scratch);
    P.s      = (uint32_t*)scratch;
    if (CARVEOUT >= 0)
        cudaFuncSetAttribute(fused_decode_kernel, cudaFuncAttributePreferredSharedMemoryCarveout, CARVEOUT);
    fused_decode_kernel<<<GRID, THREADS, SMEM_PAD, cudaStreamPerThread>>>(P);
}
```

```cpp
#include <cuda_runtime.h>
#include <cuda_bf16.h>
#include <stdint.h>

#define PROF(slot)
#define PROF_DECL
#define PROF_FLUSH(t, mask)

namespace {

constexpr int D_MODEL = 640;
constexpr int NHEAD   = 32;
constexpr int DH      = 192;
constexpr int SK      = 32768;
constexpr int WIN     = 4096;
constexpr int FF      = 1536;

constexpr int DATA_WARPS = 6;
constexpr int THREADS = 256;
constexpr int KROWS   = 64;
constexpr int OROWS   = 192;
constexpr int NDS     = D_MODEL / KROWS;
constexpr int NPCOL   = NHEAD * DH + 2 * FF;
constexpr int KT      = WIN / KROWS;
constexpr int NCB     = D_MODEL / 64;
constexpr int NWD     = FF / OROWS;
constexpr int TILE_BYTES = DATA_WARPS * 4096;

#define S_DIST 6
#define C_DIST 5
#define STAGGER 11
#define STAG_P0 40
#define FIRST_WAVE 264
#define PGRP 8
#define PC0_POS 350
#define FIN_SEG 2
#define T_STRIP 2020
#define T_O 2330
#define T_EARLY 2500
#define T_LATE 1900
#define BACKOFF 64
constexpr int STRIP_HEADS = 2;

constexpr int N_PROJ  = (NPCOL / DH) * NDS;
constexpr int N_PRE   = N_PROJ + 2;
constexpr int PCCOL   = 3 * DH;
constexpr int SEG     = KT + 4;
constexpr int SEG_V   = NHEAD;
constexpr int SEG_O   = 2 * NHEAD;
constexpr int SEG_F   = SEG_O + FIN_SEG;
constexpr int NFROW   = NWD + NHEAD - STRIP_HEADS;
constexpr int N_FIN   = 2 * NCB;
constexpr int OPART   = KT - N_FIN;
constexpr int N_OSLOT = NFROW * NCB + N_FIN;
constexpr int GRID    = N_PRE + SEG * (SEG_O + N_OSLOT / KT) + N_OSLOT % KT;
static_assert(N_OSLOT % KT != 0 && C_DIST <= N_OSLOT / KT, "combine slots run out");
constexpr int SPIN_LIMIT = 1 << 20;
constexpr uint64_t EVICT_FIRST = 0x12F0000000000000ull;

constexpr int OFF_PP  = 0;
constexpr int OFF_F   = OFF_PP + NDS * NPCOL;
constexpr int OFF_SC  = OFF_F + NPCOL + NHEAD * DH;
constexpr int OFF_P   = OFF_SC + NHEAD * WIN;
constexpr int OFF_VP  = OFF_P + NHEAD * WIN / 2;
constexpr int OFF_FIN = OFF_VP + NHEAD * KT * DH;
constexpr int OFF_CTR = OFF_FIN + NCB * NFROW * 64;
constexpr int SCRATCH_WORDS = OFF_CTR + 32;
__device__ __align__(256) uint32_t g_scratch[SCRATCH_WORDS];

struct Params {
    const char* wq;
    const char* k;
    const char* v;
    uint32_t* s;
    const char* x;
    const char* wo;
    const char* wg;
    const char* wu;
    const char* wd;
    const char* gate_w;
    __nv_bfloat16* out;
};

template <int STRIDE>
__device__ __forceinline__ void load_tile(uint32_t sdst, const char* p) {
#pragma unroll
    for (int j = 0; j < 8; j++)
        asm volatile("cp.async.cg.shared.global.L2::cache_hint [%0], [%1], 16, %2;"
                     :: "r"((sdst ^ (j << 4)) + j * 128), "l"(p + j * STRIDE), "l"(EVICT_FIRST) : "memory");
}
__device__ __forceinline__ void ldsm4(uint32_t (&a)[4], uint32_t addr) {
    asm volatile("ldmatrix.sync.aligned.m8n8.x4.shared.b16 {%0,%1,%2,%3}, [%4];"
                 : "=r"(a[0]), "=r"(a[1]), "=r"(a[2]), "=r"(a[3]) : "r"(addr) : "memory");
}
__device__ __forceinline__ void ldsm4_t(uint32_t (&a)[4], uint32_t addr) {
    asm volatile("ldmatrix.sync.aligned.m8n8.x4.trans.shared.b16 {%0,%1,%2,%3}, [%4];"
                 : "=r"(a[0]), "=r"(a[1]), "=r"(a[2]), "=r"(a[3]) : "r"(addr) : "memory");
}
__device__ __forceinline__ void mma_bf16(float (&d)[4], const uint32_t (&a)[4], uint32_t b0, uint32_t b1) {
    asm volatile("mma.sync.aligned.m16n8k16.row.col.f32.bf16.bf16.f32 {%0,%1,%2,%3}, {%4,%5,%6,%7}, {%8,%9}, {%0,%1,%2,%3};"
                 : "+f"(d[0]), "+f"(d[1]), "+f"(d[2]), "+f"(d[3])
                 : "r"(a[0]), "r"(a[1]), "r"(a[2]), "r"(a[3]), "r"(b0), "r"(b1));
}
__device__ __forceinline__ uint32_t pack_bf(float lo, float hi) {
    uint32_t r;
    asm("cvt.rn.bf16x2.f32 %0, %1, %2;" : "=r"(r) : "f"(hi), "f"(lo));
    return r;
}
__device__ __forceinline__ float rbf(float x) { return __uint_as_float(pack_bf(0.f, x)); }
__device__ __forceinline__ float bf_lo(uint32_t w) { return __uint_as_float(w << 16); }
__device__ __forceinline__ float bf_hi(uint32_t w) { return __uint_as_float(w & 0xffff0000u); }
__device__ __forceinline__ float asf(uint32_t w) { return __uint_as_float(w); }
__device__ __forceinline__ float untag(uint32_t w) { return __uint_as_float(w & ~1u); }
__device__ __forceinline__ float ex2(float x) {
    float y;
    asm("ex2.approx.ftz.f32 %0, %1;" : "=f"(y) : "f"(x));
    return y;
}
constexpr float LOG2E = 1.4426950408889634f;

__device__ __forceinline__ uint32_t ld_rlx(const uint32_t* p) {
    uint32_t v;
    asm volatile("ld.relaxed.gpu.global.u32 %0, [%1];" : "=r"(v) : "l"(p) : "memory");
    return v;
}
__device__ __forceinline__ uint4 ld_rlx4(const uint32_t* p) {
    uint4 v;
    asm volatile("ld.relaxed.gpu.global.v4.u32 {%0,%1,%2,%3}, [%4];"
                 : "=r"(v.x), "=r"(v.y), "=r"(v.z), "=r"(v.w) : "l"(p) : "memory");
    return v;
}
__device__ __forceinline__ void ld_rlx4_if(uint4& v, const uint32_t* p, uint32_t cond) {
    asm volatile("{ .reg .pred p; .reg .b32 t; and.b32 t, %5, 1; setp.ne.u32 p, t, 0;\n"
                 "@p ld.relaxed.gpu.global.v4.u32 {%0,%1,%2,%3}, [%4]; }"
                 : "+r"(v.x), "+r"(v.y), "+r"(v.z), "+r"(v.w) : "l"(p), "r"(cond) : "memory");
}
__device__ __forceinline__ void st_tag(uint32_t* p, float val, uint32_t tag) {
    const uint32_t w = (__float_as_uint(val) & ~1u) | tag;
    asm volatile("st.relaxed.gpu.global.u32 [%0], %1;" :: "l"(p), "r"(w) : "memory");
}
__device__ __forceinline__ uint32_t cur_tag(const uint32_t* s) { return (ld_rlx(s + OFF_CTR) >= N_FIN) ? 0u : 1u; }
__device__ __forceinline__ uint32_t bad4(const uint4& v, uint32_t tag) {
    return ((v.x ^ tag) | (v.y ^ tag)) | ((v.z ^ tag) | (v.w ^ tag));
}
template <int SLEEP, int N>
__device__ __forceinline__ void settle_n(uint4 (&t)[N], uint32_t tag, const uint32_t* src, int stride) {
#pragma unroll 1
    for (int it = 0; it < SPIN_LIMIT; it++) {
        uint32_t bad[N], any = 0;
#pragma unroll
        for (int j = 0; j < N; j++) { bad[j] = bad4(t[j], tag); any |= bad[j]; }
        if (!__any_sync(0xffffffffu, any & 1u)) break;
        if (SLEEP) __nanosleep(SLEEP);
#pragma unroll
        for (int j = 0; j < N; j++) ld_rlx4_if(t[j], src + j * stride, bad[j]);
    }
}
template <int N>
__device__ __forceinline__ uint32_t fetch_n(uint4 (&t)[N], const uint32_t* s, const uint32_t* src, int stride) {
#pragma unroll
    for (int j = 0; j < N; j++) t[j] = ld_rlx4(src + j * stride);
    const uint32_t tag = cur_tag(s);
    settle_n<BACKOFF>(t, tag, src, stride);
    return tag;
}
template <int N>
__device__ __forceinline__ float4 sum_n(const uint4 (&t)[N]) {
    float4 a = make_float4(untag(t[0].x), untag(t[0].y), untag(t[0].z), untag(t[0].w));
    float4 b = make_float4(untag(t[1].x), untag(t[1].y), untag(t[1].z), untag(t[1].w));
#pragma unroll
    for (int j = 2; j < N; j += 2) {
        a.x += untag(t[j].x); a.y += untag(t[j].y); a.z += untag(t[j].z); a.w += untag(t[j].w);
        b.x += untag(t[j + 1].x); b.y += untag(t[j + 1].y); b.z += untag(t[j + 1].z); b.w += untag(t[j + 1].w);
    }
    return make_float4(a.x + b.x, a.y + b.y, a.z + b.z, a.w + b.w);
}
__device__ __forceinline__ uint32_t now_ns() {
    uint32_t t;
    asm volatile("mov.u32 %0, %globaltimer_lo;" : "=r"(t) :: "memory");
    return t;
}
__device__ __forceinline__ void wait_ns(uint32_t t0, int ns) {
    for (int it = 0; it < SPIN_LIMIT && (int)(now_ns() - t0) < ns; it++) {}
}
__device__ __forceinline__ void bar_sync(int id, int n) { asm volatile("bar.sync %0, %1;" :: "r"(id), "r"(n) : "memory"); }
__device__ __forceinline__ void bar_arrive(int id, int n) { asm volatile("bar.arrive %0, %1;" :: "r"(id), "r"(n) : "memory"); }

__device__ __forceinline__ void out_tile(int n, int r, int& rb, int& cbk) {
    const int o = (n - SEG_O) * KT + r - (n > SEG_F ? N_FIN : 0);
    rb = o / NCB;
    cbk = o - rb * NCB;
}

__global__ void __launch_bounds__(THREADS, 2)
fused_decode_kernel(const Params P) {
    extern __shared__ __align__(1024) char s_tile[];
    __shared__ __align__(16) float s_red[8 * 64];
    __shared__ __align__(16) uint32_t s_w[STRIP_HEADS * DH / 2];
    __shared__ float s_misc[16];
    __shared__ uint32_t s_tag;

    const int tid = threadIdx.x;
    const int b = blockIdx.x;
    PROF_DECL;
    PROF(0);
    const uint32_t bs = (uint32_t)(b + (8 * SEG - N_PRE));
    int n = (int)(bs / SEG), r = (int)(bs - n * SEG);
    n -= 8;
    if (n < 0) r = b - (b >= PC0_POS + 2 ? 2 : 0);
    const bool tile = (n < 0) ? ((uint32_t)(b - PC0_POS) >= 2u) : (r < ((n == SEG_F) ? OPART : KT));

    if (!tile || tid >= DATA_WARPS * 32) {
        const int lane = tid & 31, warp = tid >> 5;
        if (tile) {
            const int dt = tid - DATA_WARPS * 32;
            PROF(4);
            uint32_t tag = 0;
            if (n < 0) {
                if (dt < 32) {
                    const uint32_t xv = *reinterpret_cast<const uint32_t*>(P.x + (((r / PGRP) % NDS) * KROWS + dt * 2) * 2);
                    tag = cur_tag(P.s);
                    s_w[dt] = xv;
                }
            } else if (n >= SEG_V && n < SEG_O) {
                if (dt < 32) {
                    const uint32_t* src = &P.s[OFF_P + ((n - SEG_V) * KT + r) * (KROWS / 2) + lane];
                    uint32_t t = ld_rlx(src);
                    tag = cur_tag(P.s);
#pragma unroll 1
                    for (int it = 0; it < SPIN_LIMIT && __any_sync(0xffffffffu, (t >> 31) != tag); it++) {
                        __nanosleep(BACKOFF);
                        t = ld_rlx(src);
                    }
                    s_w[lane] = t & 0x7fffffffu;
                }
            } else {
                int rb = n, cbk;
                bool ffn = false;
                if (n >= SEG_O) {
                    out_tile(n, r, rb, cbk);
                    ffn = rb < NWD;
                    rb += ffn ? NHEAD : NPCOL / DH - NWD;
                }
                const int dc = min(dt, DH / 4 - 1) * 4;
                const uint32_t* src = &P.s[OFF_F + rb * DH + dc];
                uint4 t[2];
                t[0] = ld_rlx4(src);
                t[1] = t[0];
                if (ffn) t[1] = ld_rlx4(src + FF);
                tag = cur_tag(P.s);
                settle_n<BACKOFF>(t, tag, src, ffn ? FF : 0);
                float4 q = make_float4(untag(t[0].x), untag(t[0].y), untag(t[0].z), untag(t[0].w));
                if (ffn) {
                    q.x = q.x * (q.x > 0.f ? 1.f : 0.f) * untag(t[1].x);
                    q.y = q.y * (q.y > 0.f ? 1.f : 0.f) * untag(t[1].y);
                    q.z = q.z * (q.z > 0.f ? 1.f : 0.f) * untag(t[1].z);
                    q.w = q.w * (q.w > 0.f ? 1.f : 0.f) * untag(t[1].w);
                }
                *reinterpret_cast<uint2*>(&s_w[dc >> 1]) = make_uint2(pack_bf(q.x, q.y), pack_bf(q.z, q.w));
            }
            if (dt == 0) s_tag = tag;
            __syncwarp();
            PROF(1);
            bar_arrive(1, THREADS);
            PROF_FLUSH(DATA_WARPS * 32, 0x12);
            return;
        }

        const uint32_t t_start = now_ns();
        const int e = r - KT;
        const int h = n - (e < 3 ? SEG_V + C_DIST : S_DIST);
        if (n < 0 || (e < 2 && n < NPCOL / (2 * PCCOL) - 1)) {
            if (warp < (PCCOL / 4 + 31) / 32) {
                const int col = (n < 0 ? b - PC0_POS : 2 * n + 2 + e) * PCCOL + min(tid, PCCOL / 4 - 1) * 4;
                uint4 t[NDS];
                const uint32_t tag = fetch_n(t, P.s, &P.s[OFF_PP + col], NPCOL);
                const float4 v = sum_n(t);
                asm volatile("st.relaxed.gpu.global.v4.u32 [%0], {%1,%2,%3,%4};" :: "l"(&P.s[OFF_F + col]),
                             "r"(__float_as_uint(rbf(v.x)) | tag), "r"(__float_as_uint(rbf(v.y)) | tag),
                             "r"(__float_as_uint(rbf(v.z)) | tag), "r"(__float_as_uint(rbf(v.w)) | tag) : "memory");
            }
        } else if (e < 0) {
            const int fj = r - OPART;
            const uint32_t t0 = t_start - fj * 5;
            const uint32_t tag = cur_tag(P.s);
            if (warp < DATA_WARPS) {
                constexpr int WROWS = 32 * STRIP_HEADS;
                const int row0 = (NHEAD - STRIP_HEADS) * DH + warp * WROWS;
                const uint32_t s_warp = (uint32_t)__cvta_generic_to_shared(s_tile) + warp * (WROWS * 64);
                const uint32_t sdst = s_warp + (lane >> 2) * 64 + (((lane & 3) ^ (lane >> 3)) << 4);
                const char* gsrc = P.wo + (uint32_t)((row0 + (lane >> 2)) * (D_MODEL * 2) + fj * 64 + (lane & 3) * 16);
                const uint32_t a_addr = s_warp + ((lane & 7) + ((lane >> 4) << 3)) * 64 + ((((lane >> 3) & 1) ^ ((lane & 7) >> 1)) << 4);
                uint32_t* sw = s_w + warp * (WROWS / 2);
                const int g = lane >> 2, t = lane & 3;
#pragma unroll 1
                for (int pass = 0; pass < 2; pass++) {
                    if (pass) wait_ns(t0, T_STRIP);
                    PROF(7);
#pragma unroll
                    for (int i = 0; i < WROWS / 8; i++)
                        asm volatile("{ .reg .pred p; setp.ne.s32 p, %3, 0;\n"
                                     "@p cp.async.cg.shared.global.L2::cache_hint.L2::128B [%0], [%1], 16, %2; }"
                                     :: "r"(sdst + i * 512), "l"(gsrc + i * 8 * (D_MODEL * 2)), "l"(EVICT_FIRST), "r"(pass) : "memory");
                    PROF(1);
                    if (pass) wait_ns(t0, T_O);
                    uint4 o[1];
                    const uint32_t z = tag ^ (uint32_t)(pass && lane < WROWS / 4);
                    o[0] = make_uint4(z, z, z, z);
                    settle_n<0>(o, tag, &P.s[OFF_F + NPCOL + row0 + lane * 4], 0);
                    if (lane < WROWS / 4)
                        *reinterpret_cast<uint2*>(&sw[lane * 2]) =
                            make_uint2(__byte_perm(o[0].x, o[0].y, 0x7632), __byte_perm(o[0].z, o[0].w, 0x7632));
                    __syncwarp();
                    uint32_t w[WROWS / 8];
#pragma unroll
                    for (int i = 0; i < WROWS / 8; i++) w[i] = sw[i * 4 + t];
                    float acc[4][4];
#pragma unroll
                    for (int i = 0; i < 4; i++) acc[i][0] = acc[i][1] = acc[i][2] = acc[i][3] = 0.f;
                    PROF(5);
                    asm volatile("cp.async.wait_all;" ::: "memory");
                    __syncwarp();
                    PROF(6);
#pragma unroll
                    for (int ks = 0; ks < WROWS / 16; ks++)
#pragma unroll
                        for (int i = 0; i < 2; i++) {
                            uint32_t a[4];
                            ldsm4_t(a, (a_addr ^ (i << 5)) + ks * 1024);
                            mma_bf16(acc[(ks & 1) * 2 + i], a, w[2 * ks], w[2 * ks + 1]);
                        }
                    s_red[warp * 32 + t * 8 + g] = (t & 2) ? ((t & 1) ? acc[1][2] + acc[3][2] : acc[1][0] + acc[3][0])
                                                           : ((t & 1) ? acc[0][2] + acc[2][2] : acc[0][0] + acc[2][0]);
                    bar_arrive(3 + pass, THREADS);
                }
                PROF(2);
                PROF_FLUSH(0, 0xe7);
                return;
            }
            constexpr int NEARLY = NFROW - 8;
            const uint32_t* src = &P.s[OFF_FIN + ((fj >> 1) * NFROW + (lane >> 3)) * 64 + (fj & 1) * 32 + (lane & 7) * 4];
            const bool b16 = lane & 16, b8 = lane & 8;
            const int mycol = (lane & 7) * 4 + (lane >> 3);
            auto fold = [&](const float4& v) {
                const float e0 = (b16 ? v.z : v.x) + __shfl_xor_sync(0xffffffffu, b16 ? v.x : v.z, 16);
                const float e1 = (b16 ? v.w : v.y) + __shfl_xor_sync(0xffffffffu, b16 ? v.y : v.w, 16);
                return (b8 ? e1 : e0) + __shfl_xor_sync(0xffffffffu, b8 ? e0 : e1, 8);
            };
            float gg;
            {
                const uint32_t* xb = reinterpret_cast<const uint32_t*>(P.x);
                const uint32_t* gb = reinterpret_cast<const uint32_t*>(P.gate_w);
                float s = 0.f;
#pragma unroll
                for (int j = 0; j < D_MODEL / 64; j++) {
                    const uint32_t xv = xb[j * 32 + lane], gv = gb[j * 32 + lane];
                    s += rbf(bf_lo(xv) * bf_lo(gv)) + rbf(bf_hi(xv) * bf_hi(gv));
                }
#pragma unroll
                for (int o = 16; o; o >>= 1) s += __shfl_xor_sync(0xffffffffu, s, o);
                gg = rbf(1.f / (1.f + __expf(-rbf(s))));
            }
            if (warp == DATA_WARPS) {
#pragma unroll 1
                for (int pass = 0; pass < 2; pass++) {
                    uint4 t[8];
#pragma unroll
                    for (int j = 0; j < 8; j++) {
                        const uint32_t z = tag ^ (uint32_t)(pass && 4 * j + (lane >> 3) < NEARLY);
                        t[j] = make_uint4(z, z, z, z);
                    }
                    if (pass) wait_ns(t0, T_EARLY);
                    settle_n<0>(t, tag, src, 4 * 64);
                    const float bsum = fold(make_float4(asf(t[0].x) + asf(t[1].x), asf(t[0].y) + asf(t[1].y),
                                                        asf(t[0].z) + asf(t[1].z), asf(t[0].w) + asf(t[1].w)));
                    const float asum = fold(make_float4(
                        (asf(t[2].x) + asf(t[3].x)) + (asf(t[4].x) + asf(t[5].x)) + (asf(t[6].x) + asf(t[7].x)),
                        (asf(t[2].y) + asf(t[3].y)) + (asf(t[4].y) + asf(t[5].y)) + (asf(t[6].y) + asf(t[7].y)),
                        (asf(t[2].z) + asf(t[3].z)) + (asf(t[4].z) + asf(t[5].z)) + (asf(t[6].z) + asf(t[7].z)),
                        (asf(t[2].w) + asf(t[3].w)) + (asf(t[4].w) + asf(t[5].w)) + (asf(t[6].w) + asf(t[7].w))));
                    s_red[6 * 32 + mycol] = asum;
                    s_red[7 * 32 + mycol] = rbf(rbf(1.f - gg) * rbf(bsum));
                    bar_arrive(3 + pass, THREADS);
                }
                return;
            }
#pragma unroll 1
            for (int pass = 0; pass < 2; pass++) {
                uint4 t[2];
                const uint32_t z = tag ^ (uint32_t)pass;
                t[0] = t[1] = make_uint4(z, z, z, z);
                if (pass) wait_ns(t0, T_LATE);
                settle_n<0>(t, tag, src + NEARLY * 64, 4 * 64);
                PROF(4);
                bar_sync(3 + pass, THREADS);
                const float rest = ((s_red[mycol] + s_red[32 + mycol]) + (s_red[64 + mycol] + s_red[96 + mycol])) +
                                   ((s_red[128 + mycol] + s_red[160 + mycol]) + s_red[192 + mycol]);
                const float mb = s_red[224 + mycol];
                const float a = rest + fold(make_float4(asf(t[0].x) + asf(t[1].x), asf(t[0].y) + asf(t[1].y),
                                                        asf(t[0].z) + asf(t[1].z), asf(t[0].w) + asf(t[1].w)));
                const unsigned short res = (unsigned short)pack_bf(rbf(gg * rbf(a)) + mb, 0.f);
                asm volatile("{ .reg .pred p; setp.ne.s32 p, %2, 0; @p st.global.u16 [%0], %1; }"
                             :: "l"(P.out + fj * 32 + mycol), "h"(res), "r"(pass) : "memory");
            }
            if (lane == 0)
                asm volatile("red.relaxed.gpu.global.inc.u32 [%0], %1;" :: "l"(P.s + OFF_CTR), "r"(2 * N_FIN - 1) : "memory");
            PROF(3);
            PROF_FLUSH(DATA_WARPS * 32 + 32, 0x18);
            return;
        } else if (h < 0 || h >= NHEAD) {
        } else if (e < 3) {
            const int pg = tid >> 4, c4 = tid & 15;
            uint4 t[4];
            const uint32_t tag = fetch_n(t, P.s, &P.s[OFF_VP + (h * KT + pg * 4) * DH + e * 64 + c4 * 4], DH);
            float4 acc = sum_n(t);
            acc.x += __shfl_xor_sync(0xffffffffu, acc.x, 16);
            acc.y += __shfl_xor_sync(0xffffffffu, acc.y, 16);
            acc.z += __shfl_xor_sync(0xffffffffu, acc.z, 16);
            acc.w += __shfl_xor_sync(0xffffffffu, acc.w, 16);
            if (lane < 16) *reinterpret_cast<float4*>(&s_red[warp * 64 + c4 * 4]) = acc;
            __syncthreads();
            if (tid < 64) {
                float s = 0.f;
#pragma unroll
                for (int j = 0; j < 8; j++) s += s_red[j * 64 + tid];
                st_tag(&P.s[OFF_F + NPCOL + h * DH + e * 64 + tid], rbf(s), tag);
            }
        } else {
            uint4 t[4];
            const uint32_t tag = fetch_n(t, P.s, &P.s[OFF_SC + h * WIN + tid * 4], THREADS * 4);
            float m = -INFINITY;
#pragma unroll
            for (int j = 0; j < 4; j++)
                m = fmaxf(fmaxf(m, fmaxf(untag(t[j].x), untag(t[j].y))), fmaxf(untag(t[j].z), untag(t[j].w)));
#pragma unroll
            for (int o = 16; o; o >>= 1) m = fmaxf(m, __shfl_xor_sync(0xffffffffu, m, o));
            if (lane == 0) s_misc[warp] = m;
            __syncthreads();
#pragma unroll
            for (int j = 0; j < 8; j++) m = fmaxf(m, s_misc[j]);
            float pe[4][4], l = 0.f;
#pragma unroll
            for (int j = 0; j < 4; j++) {
                pe[j][0] = ex2((untag(t[j].x) - m) * LOG2E); pe[j][1] = ex2((untag(t[j].y) - m) * LOG2E);
                pe[j][2] = ex2((untag(t[j].z) - m) * LOG2E); pe[j][3] = ex2((untag(t[j].w) - m) * LOG2E);
                l += (pe[j][0] + pe[j][1]) + (pe[j][2] + pe[j][3]);
            }
#pragma unroll
            for (int o = 16; o; o >>= 1) l += __shfl_xor_sync(0xffffffffu, l, o);
            if (lane == 0) s_misc[8 + warp] = l;
            __syncthreads();
            l = 0.f;
#pragma unroll
            for (int j = 0; j < 8; j++) l += s_misc[8 + j];
            const float il = 1.f / l;
#pragma unroll
            for (int j = 0; j < 4; j++) {
                const uint32_t p0 = (pack_bf(pe[j][0] * il, pe[j][1] * il) & 0x7fffffffu) | (tag << 31);
                const uint32_t p1 = (pack_bf(pe[j][2] * il, pe[j][3] * il) & 0x7fffffffu) | (tag << 31);
                asm volatile("st.relaxed.gpu.global.v2.u32 [%0], {%1,%2};"
                             :: "l"(&P.s[OFF_P + h * (WIN / 2) + (j * THREADS + tid) * 2]), "r"(p0), "r"(p1) : "memory");
            }
        }
        PROF(3);
        PROF_FLUSH(0, 0x09);
        return;
    }

    const int c = tid & 7, rg = tid >> 3;
    const int wr = tid >= 96;
    const int wrow = wr * 32 + (rg & 3) * 8;
    const int wcol = ((tid >> 5) - wr * 3) * 128 + c * 16;
    const uint32_t s_warp = (uint32_t)__cvta_generic_to_shared(s_tile) + (tid >> 5) * 4096;
    const uint32_t d = s_warp + (rg & 3) * 1024 + c * 16;
    uint32_t* dst;
    if (n >= SEG_O) {
        int rb, cbk;
        out_tile(n, r, rb, cbk);
        const char* w = (rb < NWD) ? P.wd : P.wo - NWD * OROWS * (D_MODEL * 2);
        load_tile<D_MODEL * 2>(d, w + (uint32_t)((rb * OROWS + rg * 8) * (D_MODEL * 2) + cbk * 128 + c * 16));
        dst = &P.s[OFF_FIN + (cbk * NFROW + rb) * 64 + tid];
    } else if (n >= 0) {
        const bool isv = n >= SEG_V;
        const int h = n & (NHEAD - 1);
        load_tile<DH * 2>(d, (isv ? P.v : P.k) + (size_t)h * (SK * DH * 2) + (uint32_t)((r * KROWS + wrow) * (DH * 2) + wcol));
        dst = isv ? &P.s[OFF_VP + (h * KT + r) * DH + tid] : &P.s[OFF_SC + h * WIN + r * KROWS + tid];
    } else {
        const int gq = r / PGRP, grp = gq / NDS, ds = gq - grp * NDS, cbk = grp * PGRP + (r - gq * PGRP);
        const int row = ds * KROWS + wrow;
        if (b < FIRST_WAVE) {
            const uint32_t t0 = clock();
            while ((int)((uint32_t)clock() - t0) < (b - STAG_P0) * STAGGER) {}
        }
        if (cbk >= NHEAD) {
            const char* w = (cbk < NHEAD + FF / DH) ? P.wg - NHEAD * (DH * 2) : P.wu - (NHEAD + FF / DH) * (DH * 2);
            load_tile<FF * 2>(d, w + (uint32_t)(row * (FF * 2) + cbk * (DH * 2) + wcol));
        } else {
            load_tile<NHEAD * DH * 2>(d, P.wq + (uint32_t)(row * (NHEAD * DH * 2) + cbk * (DH * 2) + wcol));
        }
        dst = &P.s[OFF_PP + ds * NPCOL + cbk * DH + tid];
    }
    PROF(7);
    bar_sync(1, THREADS);
    const uint32_t tag = s_tag;
    const int lane = tid & 31, warp = tid >> 5;
    const int g = lane >> 2, t = lane & 3;

    if ((uint32_t)n < (uint32_t)SEG_V) {
        const int cb = warp - wr * 3;
        uint32_t q[8];
#pragma unroll
        for (int j = 0; j < 8; j++) q[j] = s_w[cb * 32 + j * 4 + t];
        const uint32_t a_addr = s_warp + (lane & 15) * 128 + (((lane >> 4) ^ (lane & 7)) << 4);
        float acc[4][4];
#pragma unroll
        for (int i = 0; i < 4; i++) acc[i][0] = acc[i][1] = acc[i][2] = acc[i][3] = 0.f;
        asm volatile("cp.async.wait_all;" ::: "memory");
        __syncwarp();
        PROF(6);
#pragma unroll
        for (int ks = 0; ks < 4; ks++)
#pragma unroll
            for (int i = 0; i < 2; i++) {
                uint32_t a[4];
                ldsm4(a, (a_addr ^ (ks << 5)) + i * 2048);
                mma_bf16(acc[(ks & 1) * 2 + i], a, q[2 * ks], q[2 * ks + 1]);
            }
        s_red[cb * KROWS + wr * 32 + t * 8 + g] = (t & 2) ? ((t & 1) ? acc[1][2] + acc[3][2] : acc[1][0] + acc[3][0])
                                                          : ((t & 1) ? acc[0][2] + acc[2][2] : acc[0][0] + acc[2][0]);
        bar_sync(2, DATA_WARPS * 32);
        PROF(2);
        if (tid < KROWS) {
            const float u = s_red[tid] + s_red[KROWS + tid] + s_red[2 * KROWS + tid];
            st_tag(dst, rbf(rbf(u) * 0.07216878364870322f), tag);
        }
    } else {
        const bool wide = n < SEG_O;
        const int w0 = (wide ? wr : warp) * 16 + t;
        uint32_t w[4];
#pragma unroll
        for (int j = 0; j < 4; j++) w[j] = s_w[w0 + j * 4];
        const uint32_t a_addr = s_warp + ((lane & 7) + ((lane >> 4) << 3)) * 128 + ((((lane >> 3) & 1) ^ (lane & 7)) << 4);
        float acc[4][4];
#pragma unroll
        for (int i = 0; i < 4; i++) acc[i][0] = acc[i][1] = acc[i][2] = acc[i][3] = 0.f;
        asm volatile("cp.async.wait_all;" ::: "memory");
        __syncwarp();
        PROF(6);
#pragma unroll
        for (int ks = 0; ks < 2; ks++)
#pragma unroll
            for (int i = 0; i < 4; i++) {
                uint32_t a[4];
                ldsm4_t(a, (a_addr ^ (i << 5)) + ks * 2048);
                mma_bf16(acc[i], a, w[2 * ks], w[2 * ks + 1]);
            }
        s_red[warp * 64 + t * 16 + g]     = (t & 2) ? ((t & 1) ? acc[3][0] : acc[2][0]) : ((t & 1) ? acc[1][0] : acc[0][0]);
        s_red[warp * 64 + t * 16 + 8 + g] = (t & 2) ? ((t & 1) ? acc[3][2] : acc[2][2]) : ((t & 1) ? acc[1][2] : acc[0][2]);
        bar_sync(2, DATA_WARPS * 32);
        PROF(2);
        if (wide) {
            st_tag(dst, s_red[tid] + s_red[DH + tid], tag);
        } else if (tid < 64) {
            st_tag(dst, (s_red[tid] + s_red[64 + tid]) + (s_red[128 + tid] + s_red[192 + tid]) +
                        (s_red[256 + tid] + s_red[320 + tid]), tag);
        }
    }
    PROF(3);
    PROF_FLUSH(0, 0xcd);
}

}

extern "C" void kernel_launch(void* const* d_in, const int* in_sizes, int n_in, void* d_out, int out_size) {
    (void)in_sizes; (void)n_in; (void)out_size;
    Params P;
    P.x      = (const char*)d_in[0];
    P.k      = (const char*)d_in[1] + (size_t)(SK - WIN) * DH * 2;
    P.v      = (const char*)d_in[2] + (size_t)(SK - WIN) * DH * 2;
    P.wq     = (const char*)d_in[3];
    P.wo     = (const char*)d_in[4];
    P.wg     = (const char*)d_in[6];
    P.wu     = (const char*)d_in[7];
    P.wd     = (const char*)d_in[8];
    P.gate_w = (const char*)d_in[9];
    P.out    = (__nv_bfloat16*)d_out;
    void* scratch = nullptr;
    cudaGetSymbolAddress(&scratch, g_scratch);
    P.s      = (uint32_t*)scratch;
    cudaFuncSetAttribute(fused_decode_kernel, cudaFuncAttributePreferredSharedMemoryCarveout, 28);
    fused_decode_kernel<<<GRID, THREADS, TILE_BYTES, cudaStreamPerThread>>>(P);
}
```

```cpp
#include <cuda_runtime.h>
#include <cuda_bf16.h>
#include <stdint.h>

#define PROF(slot)
#define PROF_DECL
#define PROF_FLUSH(t, mask)
#define PROF_FLUSH2(t, mask)

namespace {

constexpr int D_MODEL = 640;
constexpr int NHEAD   = 32;
constexpr int DH      = 192;
constexpr int SK      = 32768;
constexpr int WIN     = 4096;
constexpr int FF      = 1536;

constexpr int DATA_WARPS = 6;
constexpr int THREADS = 256;
constexpr int KROWS   = 64;
constexpr int OROWS   = 192;
constexpr int NPCOL   = NHEAD * DH + 2 * FF;
constexpr int KT      = WIN / KROWS;
constexpr int NCB     = D_MODEL / 64;
constexpr int NWD     = FF / OROWS;
constexpr int DYN_SMEM = 70 * 1024;

#define STAGGER 15
#define STAG_P0 40
#define FIRST_WAVE 360
#define K0_WAIT 1200
#define FWR 32
#define T_W 1400
#define T_POLL 2000
#define T_CB 70
#define T_I 1500
#define OHOLD 600
#define OHOLD_R 6
#define NLATE 3
#define T_EARLY 1900
#define PG 1
#define GFIRST 0
#define KHOLD 300
#define VHOLD 0
#define OHOLD_D 1000
#define PH 1
#define XSPIN 1
#define T_I1 800
#define BACKOFF 64

constexpr int CL      = 8;
constexpr int PROWS   = D_MODEL / CL;
constexpr int C_KV    = NPCOL / DH;
constexpr int C_O     = C_KV + 2 * NHEAD * KT / CL + 8;
constexpr int FROWS   = DATA_WARPS * FWR;
constexpr int FHEADS  = CL * FROWS / DH;
constexpr int NFROW   = NHEAD - FHEADS;
constexpr int N_OUT   = NFROW * NCB;
constexpr int C_F     = C_O + (N_OUT + CL - 1) / CL;
constexpr int GRID    = (C_F + NCB) * CL;
constexpr int N_FIN   = 2 * NCB;
constexpr int SPIN_LIMIT = 1 << 20;
constexpr uint64_t EVICT_FIRST = 0x12F0000000000000ull;
constexpr int XCH_OFF = 48 * 1024;

constexpr int OFF_F   = 0;
constexpr int OFF_SC  = OFF_F + NPCOL;
constexpr int OFF_P   = OFF_SC + NHEAD * WIN;
constexpr int OFF_VP  = OFF_P + NHEAD * WIN / 2;
constexpr int OFF_FIN = OFF_VP + NHEAD * 8 * DH;
constexpr int OFF_G   = OFF_FIN + NCB * 32 * 64;
constexpr int OFF_CTR = OFF_G + 32;
constexpr int SCRATCH_WORDS = OFF_CTR + 32;
__device__ __align__(256) uint32_t g_scratch[SCRATCH_WORDS];

struct Params {
    const char* wg;
    const char* wu;
    const char* wq;
    uint32_t* s;
    const char* x;
    const char* k;
    const char* v;
    const char* wo;
    const char* wd;
    const char* gate_w;
    __nv_bfloat16* out;
};

template <int STRIDE>
__device__ __forceinline__ void load_tile(uint32_t sdst, const char* p) {
#pragma unroll
    for (int j = 0; j < 8; j++)
        asm volatile("cp.async.cg.shared.global.L2::cache_hint [%0], [%1], 16, %2;"
                     :: "r"((sdst ^ (j << 4)) + j * 128), "l"(p + j * STRIDE), "l"(EVICT_FIRST) : "memory");
}
template <int STRIDE>
__device__ __forceinline__ void load_extra(uint32_t sdst, const char* p) {
#pragma unroll
    for (int j = 0; j < 4; j++)
        asm volatile("cp.async.cg.shared.global.L2::cache_hint [%0], [%1], 16, %2;"
                     :: "r"((sdst ^ (j << 4)) + j * 128), "l"(p + j * STRIDE), "l"(EVICT_FIRST) : "memory");
}
__device__ __forceinline__ void ldsm4(uint32_t (&a)[4], uint32_t addr) {
    asm volatile("ldmatrix.sync.aligned.m8n8.x4.shared.b16 {%0,%1,%2,%3}, [%4];"
                 : "=r"(a[0]), "=r"(a[1]), "=r"(a[2]), "=r"(a[3]) : "r"(addr) : "memory");
}
__device__ __forceinline__ void ldsm4_t(uint32_t (&a)[4], uint32_t addr) {
    asm volatile("ldmatrix.sync.aligned.m8n8.x4.trans.shared.b16 {%0,%1,%2,%3}, [%4];"
                 : "=r"(a[0]), "=r"(a[1]), "=r"(a[2]), "=r"(a[3]) : "r"(addr) : "memory");
}
__device__ __forceinline__ void mma_bf16(float (&d)[4], const uint32_t (&a)[4], uint32_t b0, uint32_t b1) {
    asm volatile("mma.sync.aligned.m16n8k16.row.col.f32.bf16.bf16.f32 {%0,%1,%2,%3}, {%4,%5,%6,%7}, {%8,%9}, {%0,%1,%2,%3};"
                 : "+f"(d[0]), "+f"(d[1]), "+f"(d[2]), "+f"(d[3])
                 : "r"(a[0]), "r"(a[1]), "r"(a[2]), "r"(a[3]), "r"(b0), "r"(b1));
}
__device__ __forceinline__ uint32_t pack_bf(float lo, float hi) {
    uint32_t r;
    asm("cvt.rn.bf16x2.f32 %0, %1, %2;" : "=r"(r) : "f"(hi), "f"(lo));
    return r;
}
__device__ __forceinline__ float rbf(float x) { return __uint_as_float(pack_bf(0.f, x)); }
__device__ __forceinline__ float bf_lo(uint32_t w) { return __uint_as_float(w << 16); }
__device__ __forceinline__ float bf_hi(uint32_t w) { return __uint_as_float(w & 0xffff0000u); }
__device__ __forceinline__ float asf(uint32_t w) { return __uint_as_float(w); }
__device__ __forceinline__ float untag(uint32_t w) { return __uint_as_float(w & ~1u); }
__device__ __forceinline__ float ex2(float x) {
    float y;
    asm("ex2.approx.ftz.f32 %0, %1;" : "=f"(y) : "f"(x));
    return y;
}
constexpr float LOG2E = 1.4426950408889634f;

__device__ __forceinline__ uint32_t ld_rlx(const uint32_t* p) {
    uint32_t v;
    asm volatile("ld.relaxed.gpu.global.u32 %0, [%1];" : "=r"(v) : "l"(p) : "memory");
    return v;
}
__device__ __forceinline__ uint4 ld_rlx4(const uint32_t* p) {
    uint4 v;
    asm volatile("ld.relaxed.gpu.global.v4.u32 {%0,%1,%2,%3}, [%4];"
                 : "=r"(v.x), "=r"(v.y), "=r"(v.z), "=r"(v.w) : "l"(p) : "memory");
    return v;
}
__device__ __forceinline__ void ld_rlx4_if(uint4& v, const uint32_t* p, uint32_t cond) {
    asm volatile("{ .reg .pred p; .reg .b32 t; and.b32 t, %5, 1; setp.ne.u32 p, t, 0;\n"
                 "@p ld.relaxed.gpu.global.v4.u32 {%0,%1,%2,%3}, [%4]; }"
                 : "+r"(v.x), "+r"(v.y), "+r"(v.z), "+r"(v.w) : "l"(p), "r"(cond) : "memory");
}
__device__ __forceinline__ void st_tag(uint32_t* p, float val, uint32_t tag) {
    const uint32_t w = (__float_as_uint(val) & ~1u) | tag;
    asm volatile("st.relaxed.gpu.global.u32 [%0], %1;" :: "l"(p), "r"(w) : "memory");
}
__device__ __forceinline__ uint32_t tag_of(uint32_t ctr) { return (ctr >= N_FIN) ? 0u : 1u; }
__device__ __forceinline__ uint32_t cur_tag(const uint32_t* s) { return tag_of(ld_rlx(s + OFF_CTR)); }
__device__ __forceinline__ uint32_t bad4(const uint4& v, uint32_t tag) {
    return ((v.x ^ tag) | (v.y ^ tag)) | ((v.z ^ tag) | (v.w ^ tag));
}
template <int SLEEP, int N>
__device__ __forceinline__ void settle_n(uint4 (&t)[N], uint32_t tag, const uint32_t* src, int stride) {
#pragma unroll 1
    for (int it = 0; it < SPIN_LIMIT; it++) {
        uint32_t bad[N], any = 0;
#pragma unroll
        for (int j = 0; j < N; j++) { bad[j] = bad4(t[j], tag); any |= bad[j]; }
        if (!__any_sync(0xffffffffu, any & 1u)) break;
        if (SLEEP) __nanosleep(SLEEP);
#pragma unroll
        for (int j = 0; j < N; j++) ld_rlx4_if(t[j], src + j * stride, bad[j]);
    }
}
template <int N>
__device__ __forceinline__ uint32_t fetch_n(uint4 (&t)[N], const uint32_t* s, const uint32_t* src, int stride) {
#pragma unroll
    for (int j = 0; j < N; j++) t[j] = ld_rlx4(src + j * stride);
    const uint32_t tag = cur_tag(s);
    settle_n<BACKOFF>(t, tag, src, stride);
    return tag;
}
template <int N>
__device__ __forceinline__ float4 sum_n(const uint4 (&t)[N]) {
    float4 a = make_float4(untag(t[0].x), untag(t[0].y), untag(t[0].z), untag(t[0].w));
    float4 b = make_float4(untag(t[1].x), untag(t[1].y), untag(t[1].z), untag(t[1].w));
#pragma unroll
    for (int j = 2; j < N; j += 2) {
        a.x += untag(t[j].x); a.y += untag(t[j].y); a.z += untag(t[j].z); a.w += untag(t[j].w);
        b.x += untag(t[j + 1].x); b.y += untag(t[j + 1].y); b.z += untag(t[j + 1].z); b.w += untag(t[j + 1].w);
    }
    return make_float4(a.x + b.x, a.y + b.y, a.z + b.z, a.w + b.w);
}
__device__ __forceinline__ uint32_t now_ns() {
    uint32_t t;
    asm volatile("mov.u32 %0, %globaltimer_lo;" : "=r"(t) :: "memory");
    return t;
}
__device__ __forceinline__ void wait_ns(uint32_t t0, uint32_t c0, int ns) {
    while ((int)(now_ns() - t0) < ns && (int)((uint32_t)clock() - c0) < ns * 17 / 8) {}
}
__device__ __forceinline__ void bar_sync(int id, int n) { asm volatile("bar.sync %0, %1;" :: "r"(id), "r"(n) : "memory"); }
__device__ __forceinline__ void bar_arrive(int id, int n) { asm volatile("bar.arrive %0, %1;" :: "r"(id), "r"(n) : "memory"); }

__device__ __forceinline__ void spin_cycles(int cycles) {
    const uint32_t t0 = clock();
    while ((int)((uint32_t)clock() - t0) < cycles) {}
}
__device__ __forceinline__ void cluster_arrive() { asm volatile("barrier.cluster.arrive.relaxed.aligned;" ::: "memory"); }
__device__ __forceinline__ void cluster_wait() { asm volatile("barrier.cluster.wait.aligned;" ::: "memory"); }
__device__ __forceinline__ void send_rank0(uint32_t addr, uint32_t bar, float v) {
    asm volatile("{ .reg .b32 a, m; mapa.shared::cluster.u32 a, %0, 0; mapa.shared::cluster.u32 m, %1, 0;\n"
                 "st.async.shared::cluster.mbarrier::complete_tx::bytes.f32 [a], %2, [m]; }"
                 :: "r"(addr), "r"(bar), "f"(v) : "memory");
}
__device__ __forceinline__ void xbar_init(uint32_t bar, int bytes) {
    asm volatile("mbarrier.init.shared::cta.b64 [%0], 1;\n"
                 "mbarrier.arrive.expect_tx.shared::cta.b64 _, [%0], %1;\n"
                 "fence.mbarrier_init.release.cluster;" :: "r"(bar), "r"(bytes) : "memory");
}
__device__ __forceinline__ void xbar_wait(uint32_t bar) {
    uint32_t done = 0;
#pragma unroll 1
    for (int it = 0; it < SPIN_LIMIT && !done; it++)
        asm volatile("{ .reg .pred p; mbarrier.try_wait.parity.acquire.cluster.shared::cta.b64 p, [%1], 0; selp.u32 %0, 1, 0, p; }"
                     : "=r"(done) : "r"(bar) : "memory");
}

__device__ __forceinline__ int proj_block(int cl) {
    return cl < GFIRST ? cl + NHEAD : cl < GFIRST + NHEAD ? cl - GFIRST : cl;
}

__global__ void __launch_bounds__(THREADS, 3)
fused_decode_kernel(const Params P) {
    extern __shared__ __align__(1024) char s_tile[];
    __shared__ __align__(16) float s_red[12 * 64];
    __shared__ __align__(16) uint32_t s_w[FROWS];
    __shared__ float s_misc[16];
    __shared__ __align__(8) uint64_t s_xbar;
    __shared__ uint32_t s_tag;

    const int tid = threadIdx.x;
    const int b = blockIdx.x;
    PROF_DECL;
    PROF(0);
    if (b < C_KV * CL) {
        const int cbk = proj_block(b >> 3), row0 = (b & 7) * PROWS, hi = tid >= 96;
        if (tid >= DATA_WARPS * 32) {
            PROF(4);
            const int dt = tid - DATA_WARPS * 32;
            const uint32_t xv = reinterpret_cast<const uint32_t*>(P.x)[row0 / 2 + min(dt, PROWS / 2 - 1)];
            const uint32_t tag = cur_tag(P.s);
            if ((b & 7) == 0 && dt == 32) xbar_init((uint32_t)__cvta_generic_to_shared(&s_xbar), CL * DH * 4);
            __syncwarp();
            cluster_arrive();
            s_w[min(dt, PROWS / 2 - 1)] = xv;
            s_tag = tag;
            PROF(1);
            bar_arrive(1, THREADS);
            PROF_FLUSH(DATA_WARPS * 32, 0x12);
            return;
        }
        const uint32_t t0 = clock();
        const int row = row0 + hi * 32 + (tid & 24), rowx = row0 + 64 + ((tid & 24) >> 1);
        const uint32_t coff = ((tid >> 5) - hi * 3) * 128 + (tid & 7) * 16;
        uint32_t sd = (uint32_t)__cvta_generic_to_shared(s_tile) + (tid >> 3) * 1024 + (tid & 7) * 16;
        const uint32_t sx = (uint32_t)__cvta_generic_to_shared(s_tile) + 24576 + (tid >> 3) * 512 + (((tid & 7) ^ ((tid & 8) >> 1)) << 4);
        const int ord = (b & ~(8 * PG - 1)) + (b & 7) * PG + ((b >> 3) & (PG - 1));
        const int delay = (b < FIRST_WAVE) ? (ord - STAG_P0) * STAGGER : 0;
        if (cbk < NHEAD) {
            const char* src = P.wq + (uint32_t)(row * (NHEAD * DH * 2) + cbk * (DH * 2) + coff);
            asm volatile("" : "+l"(src), "+r"(sd));
            if (delay > 0) while ((int)((uint32_t)clock() - t0) < delay) {}
            load_tile<NHEAD * DH * 2>(sd, src);
            if (!hi) load_extra<NHEAD * DH * 2>(sx, P.wq + (uint32_t)(rowx * (NHEAD * DH * 2) + cbk * (DH * 2) + coff));
        } else {
            const char* w = ((cbk < NHEAD + FF / DH) ? P.wg - NHEAD * (DH * 2) : P.wu - (NHEAD + FF / DH) * (DH * 2)) + cbk * (DH * 2) + coff;
            const char* src = w + (uint32_t)(row * (FF * 2));
            asm volatile("" : "+l"(src), "+r"(sd));
            if (delay > 0) while ((int)((uint32_t)clock() - t0) < delay) {}
            load_tile<FF * 2>(sd, src);
            if (!hi) load_extra<FF * 2>(sx, w + (uint32_t)(rowx * (FF * 2)));
        }
    }
    const int cl = b >> 3, k = b & 7;
    const uint32_t cs = (uint32_t)(cl + (65 + 32 - C_KV));
    const int ss = (int)(cs / 65u) - 1, rem = (int)cs - (ss + 1) * 65;
    int u = ss * 64 + rem - 32, n = u >> 3;
    bool tile = rem != 64;
    if (cl < C_KV) { n = -1; u = proj_block(cl); tile = true; }
    if (cl >= C_O) { n = 64 + (cl >= C_F); u = b - C_O * CL; tile = u < N_OUT || cl >= C_F; }
    const int lane = tid & 31, warp = tid >> 5;
    const uint32_t xbar = (uint32_t)__cvta_generic_to_shared(&s_xbar);
    const uint32_t s_x = (uint32_t)__cvta_generic_to_shared(s_tile) + XCH_OFF;
    const float* xch = reinterpret_cast<const float*>(s_tile + XCH_OFF);

    if (!tile || tid >= DATA_WARPS * 32) {
        if (tile) {
            const int dt = tid - DATA_WARPS * 32;
            PROF(4);
            uint32_t tag = 0;
            if (n == 65) {
                const uint32_t t0 = now_ns() - (cl - C_F) * T_CB, c0 = clock();
                if (k == 0 && dt == 0) xbar_init(xbar, (2 * CL + 1) * 64 * 4);
                __syncwarp();
                cluster_arrive();
                tag = cur_tag(P.s);
                const uint32_t gw = ld_rlx(P.s + OFF_G);
                {
                    const int dc = min(dt, DH / 4 - 1) * 4;
                    const uint32_t* src = &P.s[OFF_F + (NHEAD + k) * DH + dc];
                    uint4 t[2];
                    t[0] = ld_rlx4(src);
                    t[1] = ld_rlx4(src + FF);
                    settle_n<BACKOFF>(t, tag, src, FF);
                    float4 q = make_float4(untag(t[0].x), untag(t[0].y), untag(t[0].z), untag(t[0].w));
                    q.x = q.x * (q.x > 0.f ? 1.f : 0.f) * untag(t[1].x);
                    q.y = q.y * (q.y > 0.f ? 1.f : 0.f) * untag(t[1].y);
                    q.z = q.z * (q.z > 0.f ? 1.f : 0.f) * untag(t[1].z);
                    q.w = q.w * (q.w > 0.f ? 1.f : 0.f) * untag(t[1].w);
                    *reinterpret_cast<uint2*>(&s_w[96 + (dc >> 1)]) = make_uint2(pack_bf(q.x, q.y), pack_bf(q.z, q.w));
                }
                wait_ns(t0, c0, T_W - (CL - 1 - k) * 450);
#pragma unroll 1
                for (int i = dt; i < (FROWS / 4 + 63) / 64 * 64; i += 64) {
                    const int row = (NHEAD - FHEADS) * DH + k * FROWS + min(i, FROWS / 4 - 1) * 4, h = row / DH;
                    const uint32_t* src = &P.s[OFF_VP + h * 7 * DH + row];
                    uint4 t[8];
#pragma unroll
                    for (int j = 0; j < 8; j++) t[j] = ld_rlx4(src + j * DH);
                    settle_n<0>(t, tag, src, DH);
                    const float4 o = sum_n(t);
                    *reinterpret_cast<uint2*>(&s_w[min(i, FROWS / 4 - 1) * 2]) = make_uint2(pack_bf(o.x, o.y), pack_bf(o.z, o.w));
                }
                __syncwarp();
                PROF(1);
                bar_arrive(1, THREADS);
                PROF_FLUSH(DATA_WARPS * 32, 0x12);
                if (k > 1) return;
                cluster_wait();
                const int cbk = cl - C_F, half = warp - DATA_WARPS;
                const uint32_t* src = &P.s[OFF_FIN + (cbk * 32 + (lane >> 3)) * 64 + half * 32 + (lane & 7) * 4];
                const bool b16 = lane & 16, b8 = lane & 8;
                const int col = half * 32 + (lane & 7) * 4 + (lane >> 3);
                auto fold = [&](const float4& v) {
                    const float e0 = (b16 ? v.z : v.x) + __shfl_xor_sync(0xffffffffu, b16 ? v.x : v.z, 16);
                    const float e1 = (b16 ? v.w : v.y) + __shfl_xor_sync(0xffffffffu, b16 ? v.y : v.w, 16);
                    return (b8 ? e1 : e0) + __shfl_xor_sync(0xffffffffu, b8 ? e0 : e1, 8);
                };
                uint32_t g = gw;
#pragma unroll 1
                for (int it = 0; it < SPIN_LIMIT && ((g ^ tag) & 1u); it++) g = ld_rlx(P.s + OFF_G);
                const float gg = untag(g), g1 = rbf(1.f - gg);
                constexpr int NE = NFROW / 4 - NLATE;
                if (k == 1) {
                    uint4 t[NE];
#pragma unroll
                    for (int j = 0; j < NE; j++) t[j] = make_uint4(tag ^ 1u, tag ^ 1u, tag ^ 1u, tag ^ 1u);
                    wait_ns(t0, c0, T_EARLY);
                    settle_n<0>(t, tag, src, 4 * 64);
                    float4 av = make_float4(asf(t[0].x), asf(t[0].y), asf(t[0].z), asf(t[0].w));
#pragma unroll
                    for (int j = 1; j < NE; j++) { av.x += asf(t[j].x); av.y += asf(t[j].y); av.z += asf(t[j].z); av.w += asf(t[j].w); }
                    send_rank0(s_x + (2 * CL * 64 + col) * 4, xbar, fold(av));
                    return;
                }
                uint4 t[NLATE];
#pragma unroll
                for (int j = 0; j < NLATE; j++) t[j] = make_uint4(tag ^ 1u, tag ^ 1u, tag ^ 1u, tag ^ 1u);
                wait_ns(t0, c0, T_POLL);
                float rest = 0.f, mb = 0.f;
                uint32_t xdone = 0;
                auto take = [&]() {
                    const float bs = ((xch[512 + col] + xch[576 + col]) + (xch[640 + col] + xch[704 + col])) +
                                     ((xch[768 + col] + xch[832 + col]) + (xch[896 + col] + xch[960 + col]));
                    rest = xch[1024 + col] + (((xch[col] + xch[64 + col]) + (xch[128 + col] + xch[192 + col])) +
                                              ((xch[256 + col] + xch[320 + col]) + (xch[384 + col] + xch[448 + col])));
                    mb = rbf(g1 * rbf(bs));
                };
#pragma unroll 1
                for (int it = 0; it < SPIN_LIMIT; it++) {
                    uint32_t bad[NLATE], any = 0;
#pragma unroll
                    for (int j = 0; j < NLATE; j++) { bad[j] = bad4(t[j], tag); any |= bad[j]; }
                    if (!__any_sync(0xffffffffu, any & 1u)) break;
#pragma unroll
                    for (int j = 0; j < NLATE; j++) ld_rlx4_if(t[j], src + (NE + j) * 4 * 64, bad[j]);
                    if (!xdone) {
                        asm volatile("{ .reg .pred p; mbarrier.test_wait.parity.acquire.cluster.shared::cta.b64 p, [%1], 0; selp.u32 %0, 1, 0, p; }"
                                     : "=r"(xdone) : "r"(xbar) : "memory");
                        xdone = __all_sync(0xffffffffu, xdone);
                        if (xdone) take();
                    }
                }
                PROF(4);
                float4 av = make_float4(asf(t[0].x), asf(t[0].y), asf(t[0].z), asf(t[0].w));
#pragma unroll
                for (int j = 1; j < NLATE; j++) { av.x += asf(t[j].x); av.y += asf(t[j].y); av.z += asf(t[j].z); av.w += asf(t[j].w); }
                const float asum = fold(av);
                if (!xdone) {
#pragma unroll 1
                    for (int it = 0; it < SPIN_LIMIT * 16 && !xdone; it++)
                        asm volatile("{ .reg .pred p; mbarrier.test_wait.parity.acquire.cluster.shared::cta.b64 p, [%1], 0; selp.u32 %0, 1, 0, p; }"
                                     : "=r"(xdone) : "r"(xbar) : "memory");
                    take();
                }
                PROF(5);
                const float a = asum + rest;
                P.out[cbk * 64 + col] = __ushort_as_bfloat16((unsigned short)pack_bf(rbf(gg * rbf(a)) + mb, 0.f));
                if (lane == 0)
                    asm volatile("red.relaxed.gpu.global.inc.u32 [%0], %1;" :: "l"(P.s + OFF_CTR), "r"(2 * N_FIN - 1) : "memory");
                PROF(3);
                { const int fj = cbk * 2 + half; PROF_FLUSH2(tid & ~31, 0x39); }
                return;
            } else if (n >= NHEAD && n < 2 * NHEAD) {
                if (dt < 32) {
                    const uint32_t* src = &P.s[OFF_P + ((u - NHEAD * 8) * CL + k) * (KROWS / 2) + lane];
                    uint32_t t = ld_rlx(src);
                    const uint32_t ctr = ld_rlx(P.s + OFF_CTR);
                    cluster_arrive();
                    tag = tag_of(ctr);
#pragma unroll 1
                    for (int it = 0; it < SPIN_LIMIT && __any_sync(0xffffffffu, (t >> 31) != tag); it++) {
                        __nanosleep(BACKOFF);
                        t = ld_rlx(src);
                    }
                    s_w[lane] = t & 0x7fffffffu;
                } else {
                    if (k == 0 && dt == 32) xbar_init(xbar, CL * DH * 4);
                    __syncwarp();
                    cluster_arrive();
                }
            } else {
                const int dc = min(dt, DH / 4 - 1) * 4;
                const int rb = u / NCB;
                if (n == 64) {
                    const uint32_t* src = &P.s[OFF_VP + rb * 8 * DH + dc];
                    uint4 t[8];
                    tag = fetch_n(t, P.s, src, DH);
                    const float4 o = sum_n(t);
                    *reinterpret_cast<uint2*>(&s_w[dc >> 1]) = make_uint2(pack_bf(o.x, o.y), pack_bf(o.z, o.w));
                } else {
                    const bool ffn = false;
                    if (n < 2) spin_cycles(K0_WAIT - (u * CL + k) * 15);
                    const uint32_t* src = &P.s[OFF_F + (ffn ? NHEAD + rb : n) * DH + dc];
                    uint4 t[2];
                    t[0] = ld_rlx4(src);
                    t[1] = t[0];
                    if (ffn) t[1] = ld_rlx4(src + FF);
                    tag = cur_tag(P.s);
                    settle_n<BACKOFF>(t, tag, src, ffn ? FF : 0);
                    float4 q = make_float4(untag(t[0].x), untag(t[0].y), untag(t[0].z), untag(t[0].w));
                    if (ffn) {
                        q.x = q.x * (q.x > 0.f ? 1.f : 0.f) * untag(t[1].x);
                        q.y = q.y * (q.y > 0.f ? 1.f : 0.f) * untag(t[1].y);
                        q.z = q.z * (q.z > 0.f ? 1.f : 0.f) * untag(t[1].z);
                        q.w = q.w * (q.w > 0.f ? 1.f : 0.f) * untag(t[1].w);
                    }
                    *reinterpret_cast<uint2*>(&s_w[dc >> 1]) = make_uint2(pack_bf(q.x, q.y), pack_bf(q.z, q.w));
                }
            }
            if (dt == 0) s_tag = tag;
            __syncwarp();
            PROF(1);
            bar_arrive(1, THREADS);
            PROF_FLUSH(DATA_WARPS * 32, 0x12);
            return;
        }

        if (n < 64 && ss == 0) {
            if (k == 2 && warp == 0) {
                const uint32_t* xb = reinterpret_cast<const uint32_t*>(P.x);
                const uint32_t* gb = reinterpret_cast<const uint32_t*>(P.gate_w);
                const uint32_t tag = cur_tag(P.s);
                float s = 0.f;
#pragma unroll
                for (int j = 0; j < D_MODEL / 64; j++) {
                    const uint32_t xv = xb[j * 32 + lane], gv = gb[j * 32 + lane];
                    s += rbf(bf_lo(xv) * bf_lo(gv)) + rbf(bf_hi(xv) * bf_hi(gv));
                }
#pragma unroll
                for (int o = 16; o; o >>= 1) s += __shfl_xor_sync(0xffffffffu, s, o);
                st_tag(&P.s[OFF_G + lane], rbf(1.f / (1.f + __expf(-rbf(s)))), tag);
            }
        } else if (n < 64 && ss >= 2 && ss < 6) {
            const int h = (ss - 2) * 8 + k;
            uint4 t[4];
            const uint32_t tag = fetch_n(t, P.s, &P.s[OFF_SC + h * WIN + tid * 4], THREADS * 4);
            if (PH && h < NFROW) {
                const uint32_t z = tag ^ 1u;
                if (tid < NCB * 16)
                    asm volatile("st.relaxed.gpu.global.v4.u32 [%0], {%1,%1,%1,%1};"
                                 :: "l"(&P.s[OFF_FIN + ((tid >> 4) * 32 + h) * 64 + (tid & 15) * 4]), "r"(z) : "memory");
                __threadfence();
            }
            float m = -INFINITY;
#pragma unroll
            for (int j = 0; j < 4; j++)
                m = fmaxf(fmaxf(m, fmaxf(untag(t[j].x), untag(t[j].y))), fmaxf(untag(t[j].z), untag(t[j].w)));
#pragma unroll
            for (int o = 16; o; o >>= 1) m = fmaxf(m, __shfl_xor_sync(0xffffffffu, m, o));
            if (lane == 0) s_misc[warp] = m;
            __syncthreads();
#pragma unroll
            for (int j = 0; j < 8; j++) m = fmaxf(m, s_misc[j]);
            float pe[4][4], l = 0.f;
#pragma unroll
            for (int j = 0; j < 4; j++) {
                pe[j][0] = ex2((untag(t[j].x) - m) * LOG2E); pe[j][1] = ex2((untag(t[j].y) - m) * LOG2E);
                pe[j][2] = ex2((untag(t[j].z) - m) * LOG2E); pe[j][3] = ex2((untag(t[j].w) - m) * LOG2E);
                l += (pe[j][0] + pe[j][1]) + (pe[j][2] + pe[j][3]);
            }
#pragma unroll
            for (int o = 16; o; o >>= 1) l += __shfl_xor_sync(0xffffffffu, l, o);
            if (lane == 0) s_misc[8 + warp] = l;
            __syncthreads();
            l = 0.f;
#pragma unroll
            for (int j = 0; j < 8; j++) l += s_misc[8 + j];
            const float il = 1.f / l;
#pragma unroll
            for (int j = 0; j < 4; j++) {
                const uint32_t p0 = (pack_bf(pe[j][0] * il, pe[j][1] * il) & 0x7fffffffu) | (tag << 31);
                const uint32_t p1 = (pack_bf(pe[j][2] * il, pe[j][3] * il) & 0x7fffffffu) | (tag << 31);
                asm volatile("st.relaxed.gpu.global.v2.u32 [%0], {%1,%2};"
                             :: "l"(&P.s[OFF_P + h * (WIN / 2) + (j * THREADS + tid) * 2]), "r"(p0), "r"(p1) : "memory");
            }
        }
        PROF(3);
        PROF_FLUSH(0, 0x09);
        return;
    }

    const int c = tid & 7, rg = tid >> 3;
    const int wr = tid >= 96;
    const int wrow = wr * 32 + (rg & 3) * 8;
    const int wcol = (warp - wr * 3) * 128 + c * 16;
    const int g = lane >> 2, t = lane & 3;
    if (n == 65) {
        const uint32_t s_warp = (uint32_t)__cvta_generic_to_shared(s_tile) + warp * (FWR * 128);
        const char* src = P.wo + (uint32_t)(((NHEAD - FHEADS) * DH + k * FROWS + warp * FWR + (rg & 3) * 8) * (D_MODEL * 2) +
                                            (cl - C_F) * 128 + c * 16);
        const uint32_t t0 = now_ns() - (cl - C_F) * T_CB, c0 = clock();
        cluster_arrive();
        wait_ns(t0, c0, T_I1);
        load_tile<D_MODEL * 2>(s_warp + 24576 + (rg & 3) * 1024 + c * 16,
                               P.wd + (uint32_t)((k * OROWS + rg * 8) * (D_MODEL * 2) + (cl - C_F) * 128 + c * 16));
        asm volatile("cp.async.commit_group;" ::: "memory");
        wait_ns(t0, c0, T_I);
        load_tile<D_MODEL * 2>(s_warp + (rg & 3) * 1024 + c * 16, src);
        asm volatile("cp.async.commit_group;" ::: "memory");
        PROF(7);
        bar_sync(1, THREADS);
        cluster_wait();
        const uint32_t a_addr = s_warp + ((lane & 7) + ((lane >> 4) << 3)) * 128 + ((((lane >> 3) & 1) ^ (lane & 7)) << 4);
#pragma unroll
        for (int part = 1; part >= 0; part--) {
            uint32_t w[4];
#pragma unroll
            for (int j = 0; j < 4; j++) w[j] = s_w[part * 96 + warp * 16 + j * 4 + t];
            float acc[4][4];
#pragma unroll
            for (int i = 0; i < 4; i++) acc[i][0] = acc[i][1] = acc[i][2] = acc[i][3] = 0.f;
            if (part) asm volatile("cp.async.wait_group 1;" ::: "memory");
            else asm volatile("cp.async.wait_group 0;" ::: "memory");
            __syncwarp();
            PROF(6);
#pragma unroll
            for (int ks = 0; ks < 2; ks++)
#pragma unroll
                for (int i = 0; i < 4; i++) {
                    uint32_t a[4];
                    ldsm4_t(a, (a_addr ^ (i << 5)) + ks * 2048 + part * 24576);
                    mma_bf16(acc[i], a, w[2 * ks], w[2 * ks + 1]);
                }
            float* red = s_red + part * 384;
            red[warp * 64 + t * 16 + g]     = (t & 2) ? ((t & 1) ? acc[3][0] : acc[2][0]) : ((t & 1) ? acc[1][0] : acc[0][0]);
            red[warp * 64 + t * 16 + 8 + g] = (t & 2) ? ((t & 1) ? acc[3][2] : acc[2][2]) : ((t & 1) ? acc[1][2] : acc[0][2]);
        }
        bar_sync(2, DATA_WARPS * 32);
        PROF(2);
        if (tid < 128) {
            const float* red = s_red + (tid >> 6) * 384 + (tid & 63);
            send_rank0(s_x + (((tid >> 6) * CL + k) * 64 + (tid & 63)) * 4, xbar,
                       (red[0] + red[64]) + (red[128] + red[192]) + (red[256] + red[320]));
        }
        PROF(3);
        PROF_FLUSH(0, 0xcd);
        return;
    }
    const uint32_t s_warp = (uint32_t)__cvta_generic_to_shared(s_tile) + warp * 4096;
    const uint32_t d = s_warp + (rg & 3) * 1024 + c * 16;
    uint32_t* dst;
    if (n == 64) {
        const int rb = u / NCB, cbk = u - rb * NCB;
        if (OHOLD) spin_cycles(min(min(u * OHOLD_R, OHOLD), (N_OUT - u) * OHOLD_D));
        load_tile<D_MODEL * 2>(d, P.wo + (uint32_t)((rb * OROWS + rg * 8) * (D_MODEL * 2) + cbk * 128 + c * 16));
        dst = &P.s[OFF_FIN + (cbk * 32 + rb) * 64 + tid];
    } else if (n >= 0) {
        const bool isv = n >= NHEAD;
        const int h = n & (NHEAD - 1), r = (u & 7) * CL + k;
        if (KHOLD || VHOLD) spin_cycles(isv ? VHOLD : KHOLD);
        load_tile<DH * 2>(d, (isv ? P.v : P.k) + (size_t)h * (SK * DH * 2) + (uint32_t)((r * KROWS + wrow) * (DH * 2) + wcol));
        dst = isv ? &P.s[OFF_VP + (u - NHEAD * 8) * DH + tid] : &P.s[OFF_SC + h * WIN + r * KROWS + tid];
        if (isv) cluster_arrive();
    } else {
        dst = &P.s[OFF_F + u * DH + tid];
        cluster_arrive();
    }
    PROF(7);
    bar_sync(1, THREADS);
    const uint32_t tag = s_tag;

    if ((uint32_t)n < (uint32_t)NHEAD) {
        const int cb = warp - wr * 3;
        uint32_t q[8];
#pragma unroll
        for (int j = 0; j < 8; j++) q[j] = s_w[cb * 32 + j * 4 + t];
        const uint32_t a_addr = s_warp + (lane & 15) * 128 + (((lane >> 4) ^ (lane & 7)) << 4);
        float acc[4][4];
#pragma unroll
        for (int i = 0; i < 4; i++) acc[i][0] = acc[i][1] = acc[i][2] = acc[i][3] = 0.f;
        asm volatile("cp.async.wait_all;" ::: "memory");
        __syncwarp();
        PROF(6);
#pragma unroll
        for (int ks = 0; ks < 4; ks++)
#pragma unroll
            for (int i = 0; i < 2; i++) {
                uint32_t a[4];
                ldsm4(a, (a_addr ^ (ks << 5)) + i * 2048);
                mma_bf16(acc[(ks & 1) * 2 + i], a, q[2 * ks], q[2 * ks + 1]);
            }
        s_red[cb * KROWS + wr * 32 + t * 8 + g] = (t & 2) ? ((t & 1) ? acc[1][2] + acc[3][2] : acc[1][0] + acc[3][0])
                                                          : ((t & 1) ? acc[0][2] + acc[2][2] : acc[0][0] + acc[2][0]);
        bar_sync(2, DATA_WARPS * 32);
        PROF(2);
        if (tid < KROWS) {
            const float v = s_red[tid] + s_red[KROWS + tid] + s_red[2 * KROWS + tid];
            st_tag(dst, rbf(rbf(v) * 0.07216878364870322f), tag);
        }
    } else {
        const bool wide = n < 64;
        const int w0 = (wide ? wr : warp) * 16 + t;
        uint32_t w[4];
#pragma unroll
        for (int j = 0; j < 4; j++) w[j] = s_w[w0 + j * 4];
        const uint32_t a_addr = s_warp + ((lane & 7) + ((lane >> 4) << 3)) * 128 + ((((lane >> 3) & 1) ^ (lane & 7)) << 4);
        float acc[4][4];
#pragma unroll
        for (int i = 0; i < 4; i++) acc[i][0] = acc[i][1] = acc[i][2] = acc[i][3] = 0.f;
        if (wide) cluster_wait();
        asm volatile("cp.async.wait_all;" ::: "memory");
        __syncwarp();
        PROF(6);
#pragma unroll
        for (int ks = 0; ks < 2; ks++)
#pragma unroll
            for (int i = 0; i < 4; i++) {
                uint32_t a[4];
                ldsm4_t(a, (a_addr ^ (i << 5)) + ks * 2048);
                mma_bf16(acc[i], a, w[2 * ks], w[2 * ks + 1]);
            }
        if (n < 0 && !wr) {
            const uint32_t w4 = s_w[32 + t], w5 = s_w[36 + t];
#pragma unroll
            for (int i = 0; i < 4; i++) {
                uint32_t a[4];
                ldsm4_t(a, (a_addr ^ (i << 5)) + 24576 - warp * 2048);
                mma_bf16(acc[i], a, w4, w5);
            }
        }
        s_red[warp * 64 + t * 16 + g]     = (t & 2) ? ((t & 1) ? acc[3][0] : acc[2][0]) : ((t & 1) ? acc[1][0] : acc[0][0]);
        s_red[warp * 64 + t * 16 + 8 + g] = (t & 2) ? ((t & 1) ? acc[3][2] : acc[2][2]) : ((t & 1) ? acc[1][2] : acc[0][2]);
        bar_sync(2, DATA_WARPS * 32);
        PROF(2);
        if (wide) {
            send_rank0(s_x + (k * DH + tid) * 4, xbar, s_red[tid] + s_red[DH + tid]);
            if (k != 0) { PROF(3); PROF_FLUSH(0, 0xcd); return; }
            xbar_wait(xbar);
            const float v = ((xch[tid] + xch[DH + tid]) + (xch[2 * DH + tid] + xch[3 * DH + tid])) +
                            ((xch[4 * DH + tid] + xch[5 * DH + tid]) + (xch[6 * DH + tid] + xch[7 * DH + tid]));
            st_tag(dst, n < 0 ? rbf(v) : v, tag);
        } else if (tid < 64) {
            st_tag(dst, (s_red[tid] + s_red[64 + tid]) + (s_red[128 + tid] + s_red[192 + tid]) +
                        (s_red[256 + tid] + s_red[320 + tid]), tag);
        }
    }
    PROF(3);
    PROF_FLUSH(0, 0xcd);
}

}

extern "C" void kernel_launch(void* const* d_in, const int* in_sizes, int n_in, void* d_out, int out_size) {
    (void)in_sizes; (void)n_in; (void)out_size;
    Params P;
    P.x      = (const char*)d_in[0];
    P.k      = (const char*)d_in[1] + (size_t)(SK - WIN) * DH * 2;
    P.v      = (const char*)d_in[2] + (size_t)(SK - WIN) * DH * 2;
    P.wq     = (const char*)d_in[3];
    P.wo     = (const char*)d_in[4];
    P.wg     = (const char*)d_in[6];
    P.wu     = (const char*)d_in[7];
    P.wd     = (const char*)d_in[8];
    P.gate_w = (const char*)d_in[9];
    P.out    = (__nv_bfloat16*)d_out;
    void* scratch = nullptr;
    cudaGetSymbolAddress(&scratch, g_scratch);
    P.s      = (uint32_t*)scratch;
    cudaFuncSetAttribute(fused_decode_kernel, cudaFuncAttributeMaxDynamicSharedMemorySize, DYN_SMEM);
    cudaLaunchConfig_t cfg = {};
    cfg.gridDim = dim3(GRID);
    cfg.blockDim = dim3(THREADS);
    cfg.dynamicSmemBytes = DYN_SMEM;
    cfg.stream = cudaStreamPerThread;
    cudaLaunchAttribute at[1];
    at[0].id = cudaLaunchAttributeClusterDimension;
    at[0].val.clusterDim.x = CL; at[0].val.clusterDim.y = 1; at[0].val.clusterDim.z = 1;
    cfg.attrs = at;
    cfg.numAttrs = 1;
    cudaLaunchKernelEx(&cfg, fused_decode_kernel, P);
}
```

```cpp
#include <cuda_runtime.h>
#include <cuda_bf16.h>
#include <stdint.h>

#define PROF(slot)
#define PROF_DECL
#define PROF_FLUSH(t, mask)
#define PROF_FLUSH2(t, mask)

namespace {

constexpr int D_MODEL = 640;
constexpr int NHEAD   = 32;
constexpr int DH      = 192;
constexpr int SK      = 32768;
constexpr int WIN     = 4096;
constexpr int FF      = 1536;

constexpr int DATA_WARPS = 6;
constexpr int THREADS = 256;
constexpr int KROWS   = 64;
constexpr int OROWS   = 192;
constexpr int NPCOL   = NHEAD * DH + 2 * FF;
constexpr int KT      = WIN / KROWS;
constexpr int NCB     = D_MODEL / 64;
constexpr int DYN_SMEM = 70 * 1024;

#define STAGGER 15
#define STAG_P0 40
#define FIRST_WAVE 360
#define K0_WAIT 1200
#define OHOLD 900
#define T_CB 75
#define T_LOAD 780
#define T_STEP 75
#define T_W 1450
#define T_POLL 2250
#define BACKOFF 64

constexpr int CL      = 8;
constexpr int PROWS   = D_MODEL / CL;
constexpr int C_KV    = NPCOL / DH;
constexpr int C_O     = C_KV + 2 * NHEAD * KT / CL + 8;
constexpr int NOH     = NHEAD - CL;
constexpr int C_F     = C_O + NOH * NCB / CL;
constexpr int GRID    = (C_F + NCB) * CL;
static_assert(NOH * NCB % CL == 0 && NOH % 4 == 0 && FF == CL * OROWS, "");
constexpr int N_FIN   = 2 * NCB;
constexpr int SPIN_LIMIT = 1 << 20;
constexpr uint64_t EVICT_FIRST = 0x12F0000000000000ull;
constexpr int BLK2    = DATA_WARPS * 4096;
constexpr int XCH_OFF = 2 * BLK2;

constexpr int OFF_F   = 0;
constexpr int OFF_SC  = OFF_F + NPCOL;
constexpr int OFF_P   = OFF_SC + NHEAD * WIN;
constexpr int OFF_VP  = OFF_P + NHEAD * WIN / 2;
constexpr int OFF_FIN = OFF_VP + NHEAD * 8 * DH;
constexpr int OFF_G   = OFF_FIN + NCB * NOH * 64;
constexpr int OFF_CTR = OFF_G + 32;
constexpr int SCRATCH_WORDS = OFF_CTR + 32;
__device__ __align__(256) uint32_t g_scratch[SCRATCH_WORDS];

struct Params {
    const char* wq;
    uint32_t* s;
    const char* x;
    const char* k;
    const char* v;
    const char* wg;
    const char* wu;
    const char* wo;
    const char* wd;
    const char* gate_w;
    __nv_bfloat16* out;
};

__device__ __forceinline__ void cp16(uint32_t sdst, const char* p) {
    asm volatile("cp.async.cg.shared.global.L2::cache_hint [%0], [%1], 16, %2;"
                 :: "r"(sdst), "l"(p), "l"(EVICT_FIRST) : "memory");
}
__device__ __forceinline__ uint32_t row_slot(uint32_t sf, int j) { return (sf ^ ((j & 1) << 6)) + j * 512; }
template <int N, int STRIDE>
__device__ __forceinline__ void load_rows(uint32_t sf, const char* p) {
#pragma unroll
    for (int j = 0; j < N; j++) cp16(row_slot(sf, j), p + j * 4 * STRIDE);
}
__device__ __forceinline__ void ldsm4(uint32_t (&a)[4], uint32_t addr) {
    asm volatile("ldmatrix.sync.aligned.m8n8.x4.shared.b16 {%0,%1,%2,%3}, [%4];"
                 : "=r"(a[0]), "=r"(a[1]), "=r"(a[2]), "=r"(a[3]) : "r"(addr) : "memory");
}
__device__ __forceinline__ void ldsm4_t(uint32_t (&a)[4], uint32_t addr) {
    asm volatile("ldmatrix.sync.aligned.m8n8.x4.trans.shared.b16 {%0,%1,%2,%3}, [%4];"
                 : "=r"(a[0]), "=r"(a[1]), "=r"(a[2]), "=r"(a[3]) : "r"(addr) : "memory");
}
__device__ __forceinline__ void mma_bf16(float (&d)[4], const uint32_t (&a)[4], uint32_t b0, uint32_t b1) {
    asm volatile("mma.sync.aligned.m16n8k16.row.col.f32.bf16.bf16.f32 {%0,%1,%2,%3}, {%4,%5,%6,%7}, {%8,%9}, {%0,%1,%2,%3};"
                 : "+f"(d[0]), "+f"(d[1]), "+f"(d[2]), "+f"(d[3])
                 : "r"(a[0]), "r"(a[1]), "r"(a[2]), "r"(a[3]), "r"(b0), "r"(b1));
}
__device__ __forceinline__ void gemv16(float (&acc)[4][4], uint32_t a_addr, uint32_t w0, uint32_t w1) {
#pragma unroll
    for (int i = 0; i < 4; i++) {
        uint32_t a[4];
        ldsm4_t(a, a_addr ^ (i << 5));
        mma_bf16(acc[i], a, w0, w1);
    }
}
__device__ __forceinline__ void store_sums(float* red, const float (&acc)[4][4], int t) {
    red[0] = (t & 2) ? ((t & 1) ? acc[3][0] : acc[2][0]) : ((t & 1) ? acc[1][0] : acc[0][0]);
    red[8] = (t & 2) ? ((t & 1) ? acc[3][2] : acc[2][2]) : ((t & 1) ? acc[1][2] : acc[0][2]);
}
template <int STRIDE>
__device__ __forceinline__ float sum6(const float* p) {
    return (p[0] + p[STRIDE]) + (p[2 * STRIDE] + p[3 * STRIDE]) + (p[4 * STRIDE] + p[5 * STRIDE]);
}
template <int STRIDE>
__device__ __forceinline__ float sum8(const float* p) {
    return ((p[0] + p[STRIDE]) + (p[2 * STRIDE] + p[3 * STRIDE])) +
           ((p[4 * STRIDE] + p[5 * STRIDE]) + (p[6 * STRIDE] + p[7 * STRIDE]));
}
__device__ __forceinline__ uint32_t pack_bf(float lo, float hi) {
    uint32_t r;
    asm("cvt.rn.bf16x2.f32 %0, %1, %2;" : "=r"(r) : "f"(hi), "f"(lo));
    return r;
}
__device__ __forceinline__ float rbf(float x) { return __uint_as_float(pack_bf(0.f, x)); }
__device__ __forceinline__ float bf_lo(uint32_t w) { return __uint_as_float(w << 16); }
__device__ __forceinline__ float bf_hi(uint32_t w) { return __uint_as_float(w & 0xffff0000u); }
__device__ __forceinline__ float untag(uint32_t w) { return __uint_as_float(w & ~1u); }
__device__ __forceinline__ float4 untag4(const uint4& v) { return make_float4(untag(v.x), untag(v.y), untag(v.z), untag(v.w)); }
__device__ __forceinline__ float ex2(float x) {
    float y;
    asm("ex2.approx.ftz.f32 %0, %1;" : "=f"(y) : "f"(x));
    return y;
}
constexpr float LOG2E = 1.4426950408889634f;

__device__ __forceinline__ uint32_t ld_rlx(const uint32_t* p) {
    uint32_t v;
    asm volatile("ld.relaxed.gpu.global.u32 %0, [%1];" : "=r"(v) : "l"(p) : "memory");
    return v;
}
__device__ __forceinline__ uint4 ld_rlx4(const uint32_t* p) {
    uint4 v;
    asm volatile("ld.relaxed.gpu.global.v4.u32 {%0,%1,%2,%3}, [%4];"
                 : "=r"(v.x), "=r"(v.y), "=r"(v.z), "=r"(v.w) : "l"(p) : "memory");
    return v;
}
__device__ __forceinline__ void ld_rlx4_if(uint4& v, const uint32_t* p, uint32_t cond) {
    asm volatile("{ .reg .pred p; .reg .b32 t; and.b32 t, %5, 1; setp.ne.u32 p, t, 0;\n"
                 "@p ld.relaxed.gpu.global.v4.u32 {%0,%1,%2,%3}, [%4]; }"
                 : "+r"(v.x), "+r"(v.y), "+r"(v.z), "+r"(v.w) : "l"(p), "r"(cond) : "memory");
}
__device__ __forceinline__ void st_tag(uint32_t* p, float val, uint32_t tag) {
    const uint32_t w = (__float_as_uint(val) & ~1u) | tag;
    asm volatile("st.relaxed.gpu.global.u32 [%0], %1;" :: "l"(p), "r"(w) : "memory");
}
__device__ __forceinline__ uint32_t tag_of(uint32_t ctr) { return (ctr >= N_FIN) ? 0u : 1u; }
__device__ __forceinline__ uint32_t cur_tag(const uint32_t* s) { return tag_of(ld_rlx(s + OFF_CTR)); }
template <int SLEEP, int N>
__device__ __forceinline__ void settle_n(uint4 (&t)[N], uint32_t tag, const uint32_t* src, int stride) {
#pragma unroll 1
    for (int it = 0; it < SPIN_LIMIT; it++) {
        uint32_t bad[N], any = 0;
#pragma unroll
        for (int j = 0; j < N; j++) {
            bad[j] = ((t[j].x ^ tag) | (t[j].y ^ tag)) | ((t[j].z ^ tag) | (t[j].w ^ tag));
            any |= bad[j];
        }
        if (!__any_sync(0xffffffffu, any & 1u)) break;
        if (SLEEP) __nanosleep(SLEEP);
#pragma unroll
        for (int j = 0; j < N; j++) ld_rlx4_if(t[j], src + j * stride, bad[j]);
    }
}
template <int N>
__device__ __forceinline__ uint32_t fetch_n(uint4 (&t)[N], const uint32_t* s, const uint32_t* src, int stride) {
#pragma unroll
    for (int j = 0; j < N; j++) t[j] = ld_rlx4(src + j * stride);
    const uint32_t tag = cur_tag(s);
    settle_n<BACKOFF>(t, tag, src, stride);
    return tag;
}
template <int N>
__device__ __forceinline__ float4 sum_n(const uint4 (&t)[N]) {
    float4 a = untag4(t[0]), b = untag4(t[1]);
#pragma unroll
    for (int j = 2; j < N; j += 2) {
        a.x += untag(t[j].x); a.y += untag(t[j].y); a.z += untag(t[j].z); a.w += untag(t[j].w);
        b.x += untag(t[j + 1].x); b.y += untag(t[j + 1].y); b.z += untag(t[j + 1].z); b.w += untag(t[j + 1].w);
    }
    return make_float4(a.x + b.x, a.y + b.y, a.z + b.z, a.w + b.w);
}
__device__ __forceinline__ uint2 pack4(const float4& v) { return make_uint2(pack_bf(v.x, v.y), pack_bf(v.z, v.w)); }

__device__ __forceinline__ uint32_t now_ns() {
    uint32_t t;
    asm volatile("mov.u32 %0, %globaltimer_lo;" : "=r"(t) :: "memory");
    return t;
}
__device__ __forceinline__ void wait_ns(uint32_t t0, uint32_t c0, int ns) {
    while ((int)(now_ns() - t0) < ns && (int)((uint32_t)clock() - c0) < ns * 17 / 8) {}
}
__device__ __forceinline__ void spin_cycles(int cycles) {
    const uint32_t t0 = clock();
    while ((int)((uint32_t)clock() - t0) < cycles) {}
}
__device__ __forceinline__ void bar_sync(int id, int n) { asm volatile("bar.sync %0, %1;" :: "r"(id), "r"(n) : "memory"); }
__device__ __forceinline__ void bar_arrive(int id, int n) { asm volatile("bar.arrive %0, %1;" :: "r"(id), "r"(n) : "memory"); }
__device__ __forceinline__ void cluster_arrive() {
    __syncwarp();
    asm volatile("barrier.cluster.arrive.relaxed.aligned;" ::: "memory");
}
__device__ __forceinline__ void cluster_wait() { asm volatile("barrier.cluster.wait.aligned;" ::: "memory"); }
__device__ __forceinline__ uint32_t at_rank0(uint32_t addr) {
    uint32_t r;
    asm("mapa.shared::cluster.u32 %0, %1, 0;" : "=r"(r) : "r"(addr));
    return r;
}
__device__ __forceinline__ void send(uint32_t raddr, uint32_t rbar, float v) {
    asm volatile("st.async.shared::cluster.mbarrier::complete_tx::bytes.f32 [%0], %2, [%1];"
                 :: "r"(raddr), "r"(rbar), "f"(v) : "memory");
}
__device__ __forceinline__ void xbar_init(uint32_t bar, int bytes) {
    asm volatile("mbarrier.init.shared::cta.b64 [%0], 1;\n"
                 "mbarrier.arrive.expect_tx.shared::cta.b64 _, [%0], %1;\n"
                 "fence.mbarrier_init.release.cluster;" :: "r"(bar), "r"(bytes) : "memory");
}
__device__ __forceinline__ void xbar_wait(uint32_t bar) {
    uint32_t done = 0;
#pragma unroll 1
    for (int it = 0; it < SPIN_LIMIT && !done; it++)
        asm volatile("{ .reg .pred p; mbarrier.try_wait.parity.acquire.cluster.shared::cta.b64 p, [%1], 0; selp.u32 %0, 1, 0, p; }"
                     : "=r"(done) : "r"(bar) : "memory");
}

__global__ void __launch_bounds__(THREADS, 3)
fused_decode_kernel(const Params P) {
    extern __shared__ __align__(1024) char s_tile[];
    __shared__ __align__(16) float s_red[2 * DATA_WARPS * 64];
    __shared__ __align__(16) uint32_t s_w[DH];
    __shared__ float s_misc[16];
    __shared__ __align__(8) uint64_t s_xbar[2];
    __shared__ uint32_t s_tag;

    const int tid = threadIdx.x;
    const int b = blockIdx.x;
    PROF_DECL;
    PROF(0);
    if (b < C_KV * CL) {
        const int cbk = b >> 3, row0 = (b & 7) * PROWS, hi = tid >= 96;
        if (tid >= DATA_WARPS * 32) {
            PROF(4);
            const int dt = min(tid - DATA_WARPS * 32, PROWS / 2 - 1);
            const uint32_t xv = reinterpret_cast<const uint32_t*>(P.x)[row0 / 2 + dt];
            const uint32_t ctr = ld_rlx(P.s + OFF_CTR);
            if ((b & 7) == 0 && dt == 32) xbar_init((uint32_t)__cvta_generic_to_shared(s_xbar), CL * DH * 4);
            cluster_arrive();
            s_w[dt] = xv;
            s_tag = tag_of(ctr);
            PROF(1);
            bar_arrive(1, THREADS);
            PROF_FLUSH(DATA_WARPS * 32, 0x12);
            return;
        }
        const uint32_t t0 = clock();
        const int g4 = (tid >> 3) & 3, row = row0 + hi * 32 + g4;
        const uint32_t coff = cbk * (DH * 2) + ((tid >> 5) - hi * 3) * 128 + (tid & 7) * 16;
        uint32_t sf = (uint32_t)__cvta_generic_to_shared(s_tile) + (tid >> 5) * 4096 + g4 * 128 + (((tid & 7) ^ g4) << 4);
        if (cbk >= NHEAD) {
            const char* src = ((cbk < NHEAD + FF / DH) ? P.wg - NHEAD * (DH * 2) : P.wu - (NHEAD + FF / DH) * (DH * 2)) +
                              (uint32_t)(row * (FF * 2) + coff);
            if (b < FIRST_WAVE) while ((int)((uint32_t)clock() - t0) < (b - STAG_P0) * STAGGER) {}
            load_rows<8, FF * 2>(sf, src);
            if (!hi) load_rows<4, FF * 2>(sf + BLK2, src + 64 * (FF * 2));
        } else {
            const char* src = P.wq + (uint32_t)(row * (NHEAD * DH * 2) + coff);
            asm volatile("" : "+l"(src), "+r"(sf));
            if (b > STAG_P0) while ((int)((uint32_t)clock() - t0) < (b - STAG_P0) * STAGGER) {}
            load_rows<8, NHEAD * DH * 2>(sf, src);
            if (!hi) load_rows<4, NHEAD * DH * 2>(sf + BLK2, src + 64 * (NHEAD * DH * 2));
        }
    }
    const int cl = b >> 3, k = b & 7;
    const uint32_t cs = (uint32_t)(cl + (65 + 32 - C_KV));
    const int ss = (int)(cs / 65u) - 1, rem = (int)cs - (ss + 1) * 65;
    int u = ss * 64 + rem - 32, n = u >> 3;
    bool tile = rem != 64;
    if (cl < C_KV) { n = -1; tile = true; }
    if (cl >= C_O) { n = 64 + (cl >= C_F); u = b - C_O * CL; tile = true; }
    const int lane = tid & 31, warp = tid >> 5;
    const uint32_t xbar = (uint32_t)__cvta_generic_to_shared(s_xbar);
    const uint32_t s_x = (uint32_t)__cvta_generic_to_shared(s_tile) + XCH_OFF;
    const float* xch = reinterpret_cast<const float*>(s_tile + XCH_OFF);

    if (!tile || tid >= DATA_WARPS * 32) {
        if (tile) {
            const int dt = tid - DATA_WARPS * 32;
            const int dc = min(dt, DH / 4 - 1) * 4;
            PROF(4);
            uint32_t tag = 0;
            if (n == 65) {
                const int cbk = cl - C_F;
                const uint32_t t0 = now_ns() - cbk * T_CB, c0 = clock();
                if (k == 0 && dt < 2) xbar_init(xbar + dt * 8, CL * 64 * 4);
                cluster_arrive();
                uint32_t g = ld_rlx(P.s + OFF_G);
                {
                    uint4 t[2];
                    tag = fetch_n(t, P.s, &P.s[OFF_F + NHEAD * DH + k * OROWS + dc], FF);
                    const float4 a = untag4(t[0]), u4 = untag4(t[1]);
                    *reinterpret_cast<uint2*>(&s_w[(DH + dc) >> 1]) =
                        pack4(make_float4(a.x * (a.x > 0.f ? 1.f : 0.f) * u4.x, a.y * (a.y > 0.f ? 1.f : 0.f) * u4.y,
                                          a.z * (a.z > 0.f ? 1.f : 0.f) * u4.z, a.w * (a.w > 0.f ? 1.f : 0.f) * u4.w));
                }
                __syncwarp();
                bar_arrive(3, THREADS);
                wait_ns(t0, c0, T_W - (CL - 1 - k) * 450);
                {
                    const uint32_t* src = &P.s[OFF_VP + (NOH + k) * 8 * DH + dc];
                    uint4 t[8];
#pragma unroll
                    for (int j = 0; j < 8; j++) t[j] = ld_rlx4(src + j * DH);
                    settle_n<0>(t, tag, src, DH);
                    *reinterpret_cast<uint2*>(&s_w[dc >> 1]) = pack4(sum_n(t));
                }
                __syncwarp();
                PROF(1);
                bar_arrive(1, THREADS);
                PROF_FLUSH(DATA_WARPS * 32, 0x12);
                if (k != 0) return;
                cluster_wait();
                const int half = warp - DATA_WARPS;
                const uint32_t* src = &P.s[OFF_FIN + (cbk * NOH + (lane >> 3)) * 64 + half * 32 + (lane & 7) * 4];
                const int col = half * 32 + (lane & 7) * 4 + (lane >> 3);
#pragma unroll 1
                for (int it = 0; it < SPIN_LIMIT && ((g ^ tag) & 1u); it++) g = ld_rlx(P.s + OFF_G);
                const float gg = untag(g);
                uint4 t[NOH / 4];
                wait_ns(t0, c0, T_POLL);
#pragma unroll
                for (int j = 0; j < NOH / 4; j++) t[j] = ld_rlx4(src + j * 4 * 64);
                settle_n<0>(t, tag, src, 4 * 64);
                PROF(4);
                const float4 v = sum_n(t);
                const bool b16 = lane & 16, b8 = lane & 8;
                const float e0 = (b16 ? v.z : v.x) + __shfl_xor_sync(0xffffffffu, b16 ? v.x : v.z, 16);
                const float e1 = (b16 ? v.w : v.y) + __shfl_xor_sync(0xffffffffu, b16 ? v.y : v.w, 16);
                const float rest = (b8 ? e1 : e0) + __shfl_xor_sync(0xffffffffu, b8 ? e0 : e1, 8);
                xbar_wait(xbar + 8);
                const float mb = rbf(rbf(1.f - gg) * rbf(sum8<64>(xch + CL * 64 + col)));
                xbar_wait(xbar);
                PROF(5);
                const float a = rest + sum8<64>(xch + col);
                P.out[cbk * 64 + col] = __ushort_as_bfloat16((unsigned short)pack_bf(rbf(gg * rbf(a)) + mb, 0.f));
                if (lane == 0)
                    asm volatile("red.relaxed.gpu.global.inc.u32 [%0], %1;" :: "l"(P.s + OFF_CTR), "r"(2 * N_FIN - 1) : "memory");
                PROF(3);
                PROF_FLUSH2(tid & ~31, 0x39);
                return;
            } else if (n >= NHEAD && n < 2 * NHEAD) {
                if (dt < 32) {
                    const uint32_t* src = &P.s[OFF_P + ((u - NHEAD * 8) * CL + k) * (KROWS / 2) + lane];
                    uint32_t t = ld_rlx(src);
                    const uint32_t ctr = ld_rlx(P.s + OFF_CTR);
                    cluster_arrive();
                    tag = tag_of(ctr);
#pragma unroll 1
                    for (int it = 0; it < SPIN_LIMIT && __any_sync(0xffffffffu, (t >> 31) != tag); it++) {
                        __nanosleep(BACKOFF);
                        t = ld_rlx(src);
                    }
                    s_w[lane] = t & 0x7fffffffu;
                } else {
                    if (k == 0 && dt == 32) xbar_init(xbar, CL * DH * 4);
                    cluster_arrive();
                }
            } else if (n < NHEAD) {
                if (n < 2) spin_cycles(K0_WAIT - (u * CL + k) * 15);
                uint4 t[1];
                tag = fetch_n(t, P.s, &P.s[OFF_F + n * DH + dc], 0);
                *reinterpret_cast<uint2*>(&s_w[dc >> 1]) = pack4(untag4(t[0]));
            } else {
                uint4 t[8];
                tag = fetch_n(t, P.s, &P.s[OFF_VP + (u / NCB) * 8 * DH + dc], DH);
                *reinterpret_cast<uint2*>(&s_w[dc >> 1]) = pack4(sum_n(t));
            }
            if (dt == 0) s_tag = tag;
            __syncwarp();
            PROF(1);
            bar_arrive(1, THREADS);
            PROF_FLUSH(DATA_WARPS * 32, 0x12);
            return;
        }

        if (ss == 0) {
            if (k == 0 && warp == 0) {
                const uint32_t* xb = reinterpret_cast<const uint32_t*>(P.x);
                const uint32_t* gb = reinterpret_cast<const uint32_t*>(P.gate_w);
                const uint32_t tag = cur_tag(P.s);
                float s = 0.f;
#pragma unroll
                for (int j = 0; j < D_MODEL / 64; j++) {
                    const uint32_t xv = xb[j * 32 + lane], gv = gb[j * 32 + lane];
                    s += rbf(bf_lo(xv) * bf_lo(gv)) + rbf(bf_hi(xv) * bf_hi(gv));
                }
#pragma unroll
                for (int o = 16; o; o >>= 1) s += __shfl_xor_sync(0xffffffffu, s, o);
                st_tag(&P.s[OFF_G + lane], rbf(1.f / (1.f + __expf(-rbf(s)))), tag);
            }
        } else if (ss >= 2 && ss < 6) {
            const int h = (ss - 2) * 8 + k;
            uint4 t[4];
            const uint32_t tag = fetch_n(t, P.s, &P.s[OFF_SC + h * WIN + tid * 4], THREADS * 4);
            float m = -INFINITY;
#pragma unroll
            for (int j = 0; j < 4; j++)
                m = fmaxf(fmaxf(m, fmaxf(untag(t[j].x), untag(t[j].y))), fmaxf(untag(t[j].z), untag(t[j].w)));
#pragma unroll
            for (int o = 16; o; o >>= 1) m = fmaxf(m, __shfl_xor_sync(0xffffffffu, m, o));
            if (lane == 0) s_misc[warp] = m;
            __syncthreads();
#pragma unroll
            for (int j = 0; j < 8; j++) m = fmaxf(m, s_misc[j]);
            float pe[4][4], l = 0.f;
#pragma unroll
            for (int j = 0; j < 4; j++) {
                pe[j][0] = ex2((untag(t[j].x) - m) * LOG2E); pe[j][1] = ex2((untag(t[j].y) - m) * LOG2E);
                pe[j][2] = ex2((untag(t[j].z) - m) * LOG2E); pe[j][3] = ex2((untag(t[j].w) - m) * LOG2E);
                l += (pe[j][0] + pe[j][1]) + (pe[j][2] + pe[j][3]);
            }
#pragma unroll
            for (int o = 16; o; o >>= 1) l += __shfl_xor_sync(0xffffffffu, l, o);
            if (lane == 0) s_misc[8 + warp] = l;
            __syncthreads();
            const float il = 1.f / sum8<1>(s_misc + 8);
#pragma unroll
            for (int j = 0; j < 4; j++) {
                const uint32_t p0 = (pack_bf(pe[j][0] * il, pe[j][1] * il) & 0x7fffffffu) | (tag << 31);
                const uint32_t p1 = (pack_bf(pe[j][2] * il, pe[j][3] * il) & 0x7fffffffu) | (tag << 31);
                asm volatile("st.relaxed.gpu.global.v2.u32 [%0], {%1,%2};"
                             :: "l"(&P.s[OFF_P + h * (WIN / 2) + (j * THREADS + tid) * 2]), "r"(p0), "r"(p1) : "memory");
            }
        }
        PROF(3);
        PROF_FLUSH(0, 0x09);
        return;
    }

    const int c = tid & 7, g4 = lane >> 3;
    const int wr = tid >= 96;
    const int g = lane >> 2, t = lane & 3;
    const uint32_t s_warp = (uint32_t)__cvta_generic_to_shared(s_tile) + warp * 4096;
    const uint32_t sf = s_warp + g4 * 128 + ((c ^ g4) << 4);
    const uint32_t at_addr = s_warp + ((lane & 7) + ((lane >> 4) << 3)) * 128 + ((((lane >> 3) & 1) ^ (lane & 7)) << 4);
    float* red = s_red + warp * 64 + t * 16 + g;
    if (n == 65) {
        const int cbk = cl - C_F;
        const uint32_t t0 = now_ns() - cbk * T_CB, c0 = clock();
        cluster_arrive();
        const uint32_t off = (uint32_t)((k * OROWS + warp * 32 + g4) * (D_MODEL * 2) + cbk * 128 + c * 16);
#pragma unroll
        for (int i = 0; i < 16; i++) {
            wait_ns(t0, c0, T_LOAD + i * T_STEP);
            cp16(row_slot(sf, i & 7) + (i < 8 ? BLK2 : 0),
                 (i < 8 ? P.wd : P.wo + NOH * DH * (D_MODEL * 2)) + off + (i & 7) * 4 * (D_MODEL * 2));
            if (i == 7 || i == 11 || i == 15) asm volatile("cp.async.commit_group;" ::: "memory");
        }
        PROF(7);
        const uint32_t raddr = at_rank0(s_x + (k * 64 + (tid & 63)) * 4), rbar = at_rank0(xbar);
        float acc[4][4];
        bar_sync(3, THREADS);
        cluster_wait();
        {
            const uint32_t* wx = s_w + DH / 2 + warp * 16 + t;
#pragma unroll
            for (int i = 0; i < 4; i++) acc[i][0] = acc[i][1] = acc[i][2] = acc[i][3] = 0.f;
            asm volatile("cp.async.wait_group 2;" ::: "memory");
            __syncwarp();
            gemv16(acc, at_addr + BLK2, wx[0], wx[4]);
            gemv16(acc, at_addr + BLK2 + 2048, wx[8], wx[12]);
            store_sums(red + DATA_WARPS * 64, acc, t);
        }
        bar_sync(2, DATA_WARPS * 32);
        if (tid < 64) send(raddr + CL * 64 * 4, rbar + 8, sum6<64>(s_red + DATA_WARPS * 64 + tid));
        bar_sync(1, THREADS);
        uint32_t w[4];
#pragma unroll
        for (int j = 0; j < 4; j++) w[j] = s_w[warp * 16 + j * 4 + t];
#pragma unroll
        for (int i = 0; i < 4; i++) acc[i][0] = acc[i][1] = acc[i][2] = acc[i][3] = 0.f;
        asm volatile("cp.async.wait_group 1;" ::: "memory");
        __syncwarp();
        gemv16(acc, at_addr, w[0], w[1]);
        asm volatile("cp.async.wait_group 0;" ::: "memory");
        __syncwarp();
        PROF(6);
        gemv16(acc, at_addr + 2048, w[2], w[3]);
        store_sums(red, acc, t);
        bar_sync(2, DATA_WARPS * 32);
        PROF(2);
        if (tid < 64) send(raddr, rbar, sum6<64>(s_red + tid));
        PROF(3);
        PROF_FLUSH(0, 0xcd);
        return;
    }
    uint32_t* dst;
    if (n == 64) {
        const int rb = u / NCB, cbk = u - rb * NCB;
        spin_cycles(min(u * 10, OHOLD));
        load_rows<8, D_MODEL * 2>(sf, P.wo + (uint32_t)((rb * OROWS + warp * 32 + g4) * (D_MODEL * 2) + cbk * 128 + c * 16));
        dst = &P.s[OFF_FIN + (cbk * NOH + rb) * 64 + tid];
    } else if (n >= 0) {
        const bool isv = n >= NHEAD;
        const int h = n & (NHEAD - 1), r = (u & 7) * CL + k;
        load_rows<8, DH * 2>(sf, (isv ? P.v : P.k) + (size_t)h * (SK * DH * 2) +
                                 (uint32_t)((r * KROWS + wr * 32 + g4) * (DH * 2) + (warp - wr * 3) * 128 + c * 16));
        dst = isv ? &P.s[OFF_VP + (u - NHEAD * 8) * DH + tid] : &P.s[OFF_SC + h * WIN + r * KROWS + tid];
        if (isv) cluster_arrive();
    } else {
        dst = &P.s[OFF_F + cl * DH + tid];
        cluster_arrive();
    }
    PROF(7);
    bar_sync(1, THREADS);
    const uint32_t tag = s_tag;
    float acc[4][4];
#pragma unroll
    for (int i = 0; i < 4; i++) acc[i][0] = acc[i][1] = acc[i][2] = acc[i][3] = 0.f;

    if ((uint32_t)n < (uint32_t)NHEAD) {
        const int cb = warp - wr * 3;
        uint32_t q[8];
#pragma unroll
        for (int j = 0; j < 8; j++) q[j] = s_w[cb * 32 + j * 4 + t];
        const uint32_t a_addr = s_warp + (lane & 15) * 128 + (((lane >> 4) ^ (lane & 7)) << 4);
        asm volatile("cp.async.wait_all;" ::: "memory");
        __syncwarp();
        PROF(6);
#pragma unroll
        for (int ks = 0; ks < 4; ks++)
#pragma unroll
            for (int i = 0; i < 2; i++) {
                uint32_t a[4];
                ldsm4(a, (a_addr ^ (ks << 5)) + i * 2048);
                mma_bf16(acc[(ks & 1) * 2 + i], a, q[2 * ks], q[2 * ks + 1]);
            }
        s_red[cb * KROWS + wr * 32 + t * 8 + g] = (t & 2) ? ((t & 1) ? acc[1][2] + acc[3][2] : acc[1][0] + acc[3][0])
                                                          : ((t & 1) ? acc[0][2] + acc[2][2] : acc[0][0] + acc[2][0]);
        bar_sync(2, DATA_WARPS * 32);
        PROF(2);
        if (tid < KROWS) {
            const float v = s_red[tid] + s_red[KROWS + tid] + s_red[2 * KROWS + tid];
            st_tag(dst, rbf(rbf(v) * 0.07216878364870322f), tag);
        }
    } else {
        const bool wide = n < 64;
        const int w0 = (wide ? wr : warp) * 16 + t;
        uint32_t w[4];
#pragma unroll
        for (int j = 0; j < 4; j++) w[j] = s_w[w0 + j * 4];
        if (wide) cluster_wait();
        asm volatile("cp.async.wait_all;" ::: "memory");
        __syncwarp();
        PROF(6);
        gemv16(acc, at_addr, w[0], w[1]);
        gemv16(acc, at_addr + 2048, w[2], w[3]);
        if (n < 0 && !wr) gemv16(acc, at_addr + BLK2, s_w[32 + t], s_w[36 + t]);
        store_sums(red, acc, t);
        bar_sync(2, DATA_WARPS * 32);
        PROF(2);
        if (wide) {
            send(at_rank0(s_x + (k * DH + tid) * 4), at_rank0(xbar), s_red[tid] + s_red[DH + tid]);
            if (k == 0) {
                xbar_wait(xbar);
                const float v = sum8<DH>(xch + tid);
                st_tag(dst, n < 0 ? rbf(v) : v, tag);
            }
        } else if (tid < 64) {
            st_tag(dst, sum6<64>(s_red + tid), tag);
        }
    }
    PROF(3);
    PROF_FLUSH(0, 0xcd);
}

}

extern "C" void kernel_launch(void* const* d_in, const int* in_sizes, int n_in, void* d_out, int out_size) {
    (void)in_sizes; (void)n_in; (void)out_size;
    Params P;
    P.x      = (const char*)d_in[0];
    P.k      = (const char*)d_in[1] + (size_t)(SK - WIN) * DH * 2;
    P.v      = (const char*)d_in[2] + (size_t)(SK - WIN) * DH * 2;
    P.wq     = (const char*)d_in[3];
    P.wo     = (const char*)d_in[4];
    P.wg     = (const char*)d_in[6];
    P.wu     = (const char*)d_in[7];
    P.wd     = (const char*)d_in[8];
    P.gate_w = (const char*)d_in[9];
    P.out    = (__nv_bfloat16*)d_out;
    void* scratch = nullptr;
    cudaGetSymbolAddress(&scratch, g_scratch);
    P.s      = (uint32_t*)scratch;
    cudaFuncSetAttribute(fused_decode_kernel, cudaFuncAttributeMaxDynamicSharedMemorySize, DYN_SMEM);
    cudaLaunchConfig_t cfg = {};
    cfg.gridDim = dim3(GRID);
    cfg.blockDim = dim3(THREADS);
    cfg.dynamicSmemBytes = DYN_SMEM;
    cfg.stream = cudaStreamPerThread;
    cudaLaunchAttribute at[1];
    at[0].id = cudaLaunchAttributeClusterDimension;
    at[0].val.clusterDim.x = CL;
    at[0].val.clusterDim.y = 1;
    at[0].val.clusterDim.z = 1;
    cfg.attrs = at;
    cfg.numAttrs = 1;
    cudaLaunchKernelEx(&cfg, fused_decode_kernel, P);
}
```

```cpp
#include <cuda_runtime.h>
#include <cuda_bf16.h>
#include <stdint.h>

namespace {

constexpr int D_MODEL = 640;
constexpr int NHEAD   = 32;
constexpr int DH      = 192;
constexpr int SK      = 32768;
constexpr int WIN     = 4096;
constexpr int FF      = 1536;

constexpr int DATA_WARPS = 6;
constexpr int THREADS = 256;
constexpr int KROWS   = 64;
constexpr int OROWS   = 192;
constexpr int NPCOL   = NHEAD * DH + 2 * FF;
constexpr int KT      = WIN / KROWS;
constexpr int NCB     = D_MODEL / 64;
constexpr int DYN_SMEM = 70 * 1024;

constexpr int FIRST_WAVE = 360;
constexpr int STAG_P0 = 40;
constexpr int STAGGER = 15;
constexpr int K0_WAIT = 1200;
constexpr int OHOLD   = 900;
constexpr int T_CB    = 75;
constexpr int T_LOAD  = 780;
constexpr int T_STEP  = 75;
constexpr int T_W     = 1450;
constexpr int T_POLL  = 2250;
constexpr int BACKOFF = 64;

constexpr int CL      = 8;
constexpr int PROWS   = D_MODEL / CL;
constexpr int C_KV    = NPCOL / DH;
constexpr int C_O     = C_KV + 2 * NHEAD * KT / CL + 8;
constexpr int NOH     = NHEAD - CL;
constexpr int C_F     = C_O + NOH * NCB / CL;
constexpr int GRID    = (C_F + NCB) * CL;
static_assert(NOH * NCB % CL == 0 && NOH % 4 == 0 && FF == CL * OROWS, "");
constexpr int N_FIN   = 2 * NCB;
constexpr int SPIN_LIMIT = 1 << 20;
constexpr int BLK2    = DATA_WARPS * 4096;
constexpr int XCH_OFF = 2 * BLK2;

constexpr int OFF_F   = 0;
constexpr int OFF_SC  = OFF_F + NPCOL;
constexpr int OFF_P   = OFF_SC + NHEAD * WIN;
constexpr int OFF_VP  = OFF_P + NHEAD * WIN / 2;
constexpr int OFF_FIN = OFF_VP + NHEAD * 8 * DH;
constexpr int OFF_G   = OFF_FIN + NCB * NOH * 64;
constexpr int OFF_CTR = OFF_G + 32;
constexpr int SCRATCH_WORDS = OFF_CTR + 32;
__device__ __align__(256) uint32_t g_scratch[SCRATCH_WORDS];

struct Params {
    const char* wq;
    uint32_t* s;
    const char* x;
    const char* k;
    const char* v;
    const char* wg;
    const char* wu;
    const char* wo;
    const char* wd;
    const char* gate_w;
    __nv_bfloat16* out;
};

__device__ __forceinline__ void cp16(uint32_t sdst, const char* p) {
    uint64_t pol;
    asm("createpolicy.fractional.L2::evict_first.b64 %0, 1.0;" : "=l"(pol));
    asm volatile("cp.async.cg.shared.global.L2::cache_hint [%0], [%1], 16, %2;"
                 :: "r"(sdst), "l"(p), "l"(pol) : "memory");
}
__device__ __forceinline__ uint32_t row_slot(uint32_t sf, int j) { return (sf ^ ((j & 1) << 6)) + j * 512; }
template <int N, int STRIDE>
__device__ __forceinline__ void load_rows(uint32_t sf, const char* p) {
#pragma unroll
    for (int j = 0; j < N; j++) cp16(row_slot(sf, j), p + j * 4 * STRIDE);
}
__device__ __forceinline__ void ldsm4(uint32_t (&a)[4], uint32_t addr) {
    asm volatile("ldmatrix.sync.aligned.m8n8.x4.shared.b16 {%0,%1,%2,%3}, [%4];"
                 : "=r"(a[0]), "=r"(a[1]), "=r"(a[2]), "=r"(a[3]) : "r"(addr) : "memory");
}
__device__ __forceinline__ void ldsm4_t(uint32_t (&a)[4], uint32_t addr) {
    asm volatile("ldmatrix.sync.aligned.m8n8.x4.trans.shared.b16 {%0,%1,%2,%3}, [%4];"
                 : "=r"(a[0]), "=r"(a[1]), "=r"(a[2]), "=r"(a[3]) : "r"(addr) : "memory");
}
__device__ __forceinline__ void mma_bf16(float (&d)[4], const uint32_t (&a)[4], uint32_t b0, uint32_t b1) {
    asm volatile("mma.sync.aligned.m16n8k16.row.col.f32.bf16.bf16.f32 {%0,%1,%2,%3}, {%4,%5,%6,%7}, {%8,%9}, {%0,%1,%2,%3};"
                 : "+f"(d[0]), "+f"(d[1]), "+f"(d[2]), "+f"(d[3])
                 : "r"(a[0]), "r"(a[1]), "r"(a[2]), "r"(a[3]), "r"(b0), "r"(b1));
}
__device__ __forceinline__ void gemv16(float (&acc)[4][4], uint32_t a_addr, uint32_t w0, uint32_t w1) {
#pragma unroll
    for (int i = 0; i < 4; i++) {
        uint32_t a[4];
        ldsm4_t(a, a_addr ^ (i << 5));
        mma_bf16(acc[i], a, w0, w1);
    }
}
__device__ __forceinline__ void store_sums(float* red, const float (&acc)[4][4], int t) {
    red[0] = (t & 2) ? ((t & 1) ? acc[3][0] : acc[2][0]) : ((t & 1) ? acc[1][0] : acc[0][0]);
    red[8] = (t & 2) ? ((t & 1) ? acc[3][2] : acc[2][2]) : ((t & 1) ? acc[1][2] : acc[0][2]);
}
template <int STRIDE>
__device__ __forceinline__ float sum6(const float* p) {
    return (p[0] + p[STRIDE]) + (p[2 * STRIDE] + p[3 * STRIDE]) + (p[4 * STRIDE] + p[5 * STRIDE]);
}
template <int STRIDE>
__device__ __forceinline__ float sum8(const float* p) {
    return ((p[0] + p[STRIDE]) + (p[2 * STRIDE] + p[3 * STRIDE])) +
           ((p[4 * STRIDE] + p[5 * STRIDE]) + (p[6 * STRIDE] + p[7 * STRIDE]));
}
__device__ __forceinline__ uint32_t pack_bf(float lo, float hi) {
    uint32_t r;
    asm("cvt.rn.bf16x2.f32 %0, %1, %2;" : "=r"(r) : "f"(hi), "f"(lo));
    return r;
}
__device__ __forceinline__ float rbf(float x) { return __uint_as_float(pack_bf(0.f, x)); }
__device__ __forceinline__ float bf_lo(uint32_t w) { return __uint_as_float(w << 16); }
__device__ __forceinline__ float bf_hi(uint32_t w) { return __uint_as_float(w & 0xffff0000u); }
__device__ __forceinline__ float untag(uint32_t w) { return __uint_as_float(w & ~1u); }
__device__ __forceinline__ float4 untag4(const uint4& v) { return make_float4(untag(v.x), untag(v.y), untag(v.z), untag(v.w)); }
__device__ __forceinline__ float ex2(float x) {
    float y;
    asm("ex2.approx.ftz.f32 %0, %1;" : "=f"(y) : "f"(x));
    return y;
}
constexpr float LOG2E = 1.4426950408889634f;

__device__ __forceinline__ uint32_t ld_rlx(const uint32_t* p) {
    uint32_t v;
    asm volatile("ld.relaxed.gpu.global.u32 %0, [%1];" : "=r"(v) : "l"(p) : "memory");
    return v;
}
__device__ __forceinline__ uint4 ld_rlx4(const uint32_t* p) {
    uint4 v;
    asm volatile("ld.relaxed.gpu.global.v4.u32 {%0,%1,%2,%3}, [%4];"
                 : "=r"(v.x), "=r"(v.y), "=r"(v.z), "=r"(v.w) : "l"(p) : "memory");
    return v;
}
__device__ __forceinline__ void ld_rlx4_if(uint4& v, const uint32_t* p, uint32_t cond) {
    asm volatile("{ .reg .pred p; .reg .b32 t; and.b32 t, %5, 1; setp.ne.u32 p, t, 0;\n"
                 "@p ld.relaxed.gpu.global.v4.u32 {%0,%1,%2,%3}, [%4]; }"
                 : "+r"(v.x), "+r"(v.y), "+r"(v.z), "+r"(v.w) : "l"(p), "r"(cond) : "memory");
}
__device__ __forceinline__ void st_tag(uint32_t* p, float val, uint32_t tag) {
    const uint32_t w = (__float_as_uint(val) & ~1u) | tag;
    asm volatile("st.relaxed.gpu.global.u32 [%0], %1;" :: "l"(p), "r"(w) : "memory");
}
__device__ __forceinline__ uint32_t tag_of(uint32_t ctr) { return (ctr >= N_FIN) ? 0u : 1u; }
__device__ __forceinline__ uint32_t cur_tag(const uint32_t* s) { return tag_of(ld_rlx(s + OFF_CTR)); }
template <int SLEEP, int N>
__device__ __forceinline__ void settle_n(uint4 (&t)[N], uint32_t tag, const uint32_t* src, int stride) {
#pragma unroll 1
    for (int it = 0; it < SPIN_LIMIT; it++) {
        uint32_t bad[N], any = 0;
#pragma unroll
        for (int j = 0; j < N; j++) {
            bad[j] = ((t[j].x ^ tag) | (t[j].y ^ tag)) | ((t[j].z ^ tag) | (t[j].w ^ tag));
            any |= bad[j];
        }
        if (!__any_sync(0xffffffffu, any & 1u)) break;
        if (SLEEP) __nanosleep(SLEEP);
#pragma unroll
        for (int j = 0; j < N; j++) ld_rlx4_if(t[j], src + j * stride, bad[j]);
    }
}
template <int N>
__device__ __forceinline__ uint32_t fetch_n(uint4 (&t)[N], const uint32_t* s, const uint32_t* src, int stride) {
#pragma unroll
    for (int j = 0; j < N; j++) t[j] = ld_rlx4(src + j * stride);
    const uint32_t tag = cur_tag(s);
    settle_n<BACKOFF>(t, tag, src, stride);
    return tag;
}
template <int N>
__device__ __forceinline__ float4 sum_n(const uint4 (&t)[N]) {
    float4 a = untag4(t[0]), b = untag4(t[1]);
#pragma unroll
    for (int j = 2; j < N; j += 2) {
        a.x += untag(t[j].x); a.y += untag(t[j].y); a.z += untag(t[j].z); a.w += untag(t[j].w);
        b.x += untag(t[j + 1].x); b.y += untag(t[j + 1].y); b.z += untag(t[j + 1].z); b.w += untag(t[j + 1].w);
    }
    return make_float4(a.x + b.x, a.y + b.y, a.z + b.z, a.w + b.w);
}
__device__ __forceinline__ uint2 pack4(const float4& v) { return make_uint2(pack_bf(v.x, v.y), pack_bf(v.z, v.w)); }

__device__ __forceinline__ uint32_t now_ns() {
    uint32_t t;
    asm volatile("mov.u32 %0, %globaltimer_lo;" : "=r"(t) :: "memory");
    return t;
}
__device__ __forceinline__ void wait_ns(uint32_t t0, uint32_t c0, int ns) {
    while ((int)(now_ns() - t0) < ns && (int)((uint32_t)clock() - c0) < ns * 17 / 8) {}
}
__device__ __forceinline__ void spin_cycles(int cycles) {
    const uint32_t t0 = clock();
    while ((int)((uint32_t)clock() - t0) < cycles) {}
}
__device__ __forceinline__ void bar_sync(int id, int n) { asm volatile("bar.sync %0, %1;" :: "r"(id), "r"(n) : "memory"); }
__device__ __forceinline__ void bar_arrive(int id, int n) { asm volatile("bar.arrive %0, %1;" :: "r"(id), "r"(n) : "memory"); }
__device__ __forceinline__ void cluster_arrive() {
    __syncwarp();
    asm volatile("barrier.cluster.arrive.relaxed.aligned;" ::: "memory");
}
__device__ __forceinline__ void cluster_wait() { asm volatile("barrier.cluster.wait.aligned;" ::: "memory"); }
__device__ __forceinline__ uint32_t at_rank0(uint32_t addr) {
    uint32_t r;
    asm("mapa.shared::cluster.u32 %0, %1, 0;" : "=r"(r) : "r"(addr));
    return r;
}
__device__ __forceinline__ void send(uint32_t raddr, uint32_t rbar, float v) {
    asm volatile("st.async.shared::cluster.mbarrier::complete_tx::bytes.f32 [%0], %2, [%1];"
                 :: "r"(raddr), "r"(rbar), "f"(v) : "memory");
}
__device__ __forceinline__ void xbar_init(uint32_t bar, int bytes) {
    asm volatile("mbarrier.init.shared::cta.b64 [%0], 1;\n"
                 "mbarrier.arrive.expect_tx.shared::cta.b64 _, [%0], %1;\n"
                 "fence.mbarrier_init.release.cluster;" :: "r"(bar), "r"(bytes) : "memory");
}
__device__ __forceinline__ void xbar_wait(uint32_t bar) {
    uint32_t done = 0;
#pragma unroll 1
    for (int it = 0; it < SPIN_LIMIT && !done; it++)
        asm volatile("{ .reg .pred p; mbarrier.try_wait.parity.acquire.cluster.shared::cta.b64 p, [%1], 0; selp.u32 %0, 1, 0, p; }"
                     : "=r"(done) : "r"(bar) : "memory");
}

__global__ void __cluster_dims__(CL, 1, 1) __launch_bounds__(THREADS, 3)
fused_decode_kernel(const Params P) {
    extern __shared__ __align__(1024) char s_tile[];
    __shared__ __align__(16) float s_red[2 * DATA_WARPS * 64];
    __shared__ __align__(16) uint32_t s_w[DH];
    __shared__ float s_misc[16];
    __shared__ __align__(8) uint64_t s_xbar[2];
    __shared__ uint32_t s_tag;

    const int tid = threadIdx.x;
    const int b = blockIdx.x;
    if (b < C_KV * CL) {
        const int cbk = b >> 3, row0 = (b & 7) * PROWS, hi = tid >= 96;
        if (tid >= DATA_WARPS * 32) {
            const int dt = min(tid - DATA_WARPS * 32, PROWS / 2 - 1);
            const uint32_t xv = reinterpret_cast<const uint32_t*>(P.x)[row0 / 2 + dt];
            const uint32_t ctr = ld_rlx(P.s + OFF_CTR);
            if ((b & 7) == 0 && dt == 32) xbar_init((uint32_t)__cvta_generic_to_shared(s_xbar), CL * DH * 4);
            cluster_arrive();
            s_w[dt] = xv;
            s_tag = tag_of(ctr);
            bar_arrive(1, THREADS);
            return;
        }
        const uint32_t t0 = clock();
        const int g4 = (tid >> 3) & 3, row = row0 + hi * 32 + g4;
        const uint32_t coff = cbk * (DH * 2) + ((tid >> 5) - hi * 3) * 128 + (tid & 7) * 16;
        uint32_t sf = (uint32_t)__cvta_generic_to_shared(s_tile) + (tid >> 5) * 4096 + g4 * 128 + (((tid & 7) ^ g4) << 4);
        if (cbk >= NHEAD) {
            const char* src = ((cbk < NHEAD + FF / DH) ? P.wg - NHEAD * (DH * 2) : P.wu - (NHEAD + FF / DH) * (DH * 2)) +
                              (uint32_t)(row * (FF * 2) + coff);
            if (b < FIRST_WAVE) while ((int)((uint32_t)clock() - t0) < (b - STAG_P0) * STAGGER) {}
            load_rows<8, FF * 2>(sf, src);
            if (!hi) load_rows<4, FF * 2>(sf + BLK2, src + 64 * (FF * 2));
        } else {
            const char* src = P.wq + (uint32_t)(row * (NHEAD * DH * 2) + coff);
            asm volatile("" : "+l"(src), "+r"(sf));
            if (b > STAG_P0) while ((int)((uint32_t)clock() - t0) < (b - STAG_P0) * STAGGER) {}
            load_rows<8, NHEAD * DH * 2>(sf, src);
            if (!hi) load_rows<4, NHEAD * DH * 2>(sf + BLK2, src + 64 * (NHEAD * DH * 2));
        }
    }
    const int cl = b >> 3, k = b & 7;
    const uint32_t cs = (uint32_t)(cl + (65 + 32 - C_KV));
    const int ss = (int)(cs / 65u) - 1, rem = (int)cs - (ss + 1) * 65;
    int u = ss * 64 + rem - 32, n = u >> 3;
    bool tile = rem != 64;
    if (cl < C_KV) { n = -1; tile = true; }
    if (cl >= C_O) { n = 64 + (cl >= C_F); u = b - C_O * CL; tile = true; }
    const int lane = tid & 31, warp = tid >> 5;
    const uint32_t xbar = (uint32_t)__cvta_generic_to_shared(s_xbar);
    const uint32_t s_x = (uint32_t)__cvta_generic_to_shared(s_tile) + XCH_OFF;
    const float* xch = reinterpret_cast<const float*>(s_tile + XCH_OFF);

    if (!tile || tid >= DATA_WARPS * 32) {
        if (tile) {
            const int dt = tid - DATA_WARPS * 32;
            const int dc = min(dt, DH / 4 - 1) * 4;
            uint32_t tag = 0;
            if (n == 65) {
                const int cbk = cl - C_F;
                const uint32_t t0 = now_ns() - cbk * T_CB, c0 = clock();
                if (k == 0 && dt < 2) xbar_init(xbar + dt * 8, CL * 64 * 4);
                cluster_arrive();
                uint32_t g = 0;
                if (k == 0) g = ld_rlx(P.s + OFF_G);
                {
                    uint4 t[2];
                    tag = fetch_n(t, P.s, &P.s[OFF_F + NHEAD * DH + k * OROWS + dc], FF);
                    const float4 a = untag4(t[0]), u4 = untag4(t[1]);
                    *reinterpret_cast<uint2*>(&s_w[(DH + dc) >> 1]) =
                        pack4(make_float4(a.x * (a.x > 0.f ? 1.f : 0.f) * u4.x, a.y * (a.y > 0.f ? 1.f : 0.f) * u4.y,
                                          a.z * (a.z > 0.f ? 1.f : 0.f) * u4.z, a.w * (a.w > 0.f ? 1.f : 0.f) * u4.w));
                }
                __syncwarp();
                bar_arrive(3, THREADS);
                wait_ns(t0, c0, T_W - (CL - 1 - k) * 450);
                {
                    const uint32_t* src = &P.s[OFF_VP + (NOH + k) * 8 * DH + dc];
                    uint4 t[8];
#pragma unroll
                    for (int j = 0; j < 8; j++) t[j] = ld_rlx4(src + j * DH);
                    settle_n<0>(t, tag, src, DH);
                    *reinterpret_cast<uint2*>(&s_w[dc >> 1]) = pack4(sum_n(t));
                }
                __syncwarp();
                bar_arrive(1, THREADS);
                if (k != 0) return;
                cluster_wait();
                const int half = warp - DATA_WARPS;
                const uint32_t* src = &P.s[OFF_FIN + (cbk * NOH + (lane >> 3)) * 64 + half * 32 + (lane & 7) * 4];
                const int col = half * 32 + (lane & 7) * 4 + (lane >> 3);
#pragma unroll 1
                for (int it = 0; it < SPIN_LIMIT && ((g ^ tag) & 1u); it++) g = ld_rlx(P.s + OFF_G);
                const float gg = untag(g);
                uint4 t[NOH / 4];
                wait_ns(t0, c0, T_POLL);
#pragma unroll
                for (int j = 0; j < NOH / 4; j++) t[j] = ld_rlx4(src + j * 4 * 64);
                settle_n<0>(t, tag, src, 4 * 64);
                const float4 v = sum_n(t);
                const bool b16 = lane & 16, b8 = lane & 8;
                const float e0 = (b16 ? v.z : v.x) + __shfl_xor_sync(0xffffffffu, b16 ? v.x : v.z, 16);
                const float e1 = (b16 ? v.w : v.y) + __shfl_xor_sync(0xffffffffu, b16 ? v.y : v.w, 16);
                const float rest = (b8 ? e1 : e0) + __shfl_xor_sync(0xffffffffu, b8 ? e0 : e1, 8);
                xbar_wait(xbar + 8);
                const float mb = rbf(rbf(1.f - gg) * rbf(sum8<64>(xch + CL * 64 + col)));
                xbar_wait(xbar);
                const float a = rest + sum8<64>(xch + col);
                P.out[cbk * 64 + col] = __ushort_as_bfloat16((unsigned short)pack_bf(rbf(gg * rbf(a)) + mb, 0.f));
                if (lane == 0)
                    asm volatile("red.relaxed.gpu.global.inc.u32 [%0], %1;" :: "l"(P.s + OFF_CTR), "r"(2 * N_FIN - 1) : "memory");
                return;
            } else if (n >= NHEAD && n < 2 * NHEAD) {
                if (dt < 32) {
                    const uint32_t* src = &P.s[OFF_P + ((u - NHEAD * 8) * CL + k) * (KROWS / 2) + lane];
                    uint32_t t = ld_rlx(src);
                    const uint32_t ctr = ld_rlx(P.s + OFF_CTR);
                    cluster_arrive();
                    tag = tag_of(ctr);
#pragma unroll 1
                    for (int it = 0; it < SPIN_LIMIT && __any_sync(0xffffffffu, (t >> 31) != tag); it++) {
                        __nanosleep(BACKOFF);
                        t = ld_rlx(src);
                    }
                    s_w[lane] = t & 0x7fffffffu;
                } else {
                    if (k == 0 && dt == 32) xbar_init(xbar, CL * DH * 4);
                    cluster_arrive();
                }
            } else if (n < NHEAD) {
                if (n < 2) spin_cycles(K0_WAIT - (u * CL + k) * 15);
                uint4 t[1];
                tag = fetch_n(t, P.s, &P.s[OFF_F + n * DH + dc], 0);
                *reinterpret_cast<uint2*>(&s_w[dc >> 1]) = pack4(untag4(t[0]));
            } else {
                uint4 t[8];
                tag = fetch_n(t, P.s, &P.s[OFF_VP + (u / NCB) * 8 * DH + dc], DH);
                *reinterpret_cast<uint2*>(&s_w[dc >> 1]) = pack4(sum_n(t));
            }
            if (dt == 0) s_tag = tag;
            __syncwarp();
            bar_arrive(1, THREADS);
            return;
        }

        if (ss == 0) {
            if (k == 0 && warp == 0) {
                const uint32_t* xb = reinterpret_cast<const uint32_t*>(P.x);
                const uint32_t* gb = reinterpret_cast<const uint32_t*>(P.gate_w);
                const uint32_t tag = cur_tag(P.s);
                float s = 0.f;
#pragma unroll
                for (int j = 0; j < D_MODEL / 64; j++) {
                    const uint32_t xv = xb[j * 32 + lane], gv = gb[j * 32 + lane];
                    s += rbf(bf_lo(xv) * bf_lo(gv)) + rbf(bf_hi(xv) * bf_hi(gv));
                }
#pragma unroll
                for (int o = 16; o; o >>= 1) s += __shfl_xor_sync(0xffffffffu, s, o);
                st_tag(&P.s[OFF_G + lane], rbf(1.f / (1.f + __expf(-rbf(s)))), tag);
            }
        } else if (ss >= 2 && ss < 6) {
            const int h = (ss - 2) * 8 + k;
            uint4 t[4];
            const uint32_t tag = fetch_n(t, P.s, &P.s[OFF_SC + h * WIN + tid * 4], THREADS * 4);
            float m = -INFINITY;
#pragma unroll
            for (int j = 0; j < 4; j++)
                m = fmaxf(fmaxf(m, fmaxf(untag(t[j].x), untag(t[j].y))), fmaxf(untag(t[j].z), untag(t[j].w)));
#pragma unroll
            for (int o = 16; o; o >>= 1) m = fmaxf(m, __shfl_xor_sync(0xffffffffu, m, o));
            if (lane == 0) s_misc[warp] = m;
            __syncthreads();
#pragma unroll
            for (int j = 0; j < 8; j++) m = fmaxf(m, s_misc[j]);
            float pe[4][4], l = 0.f;
#pragma unroll
            for (int j = 0; j < 4; j++) {
                pe[j][0] = ex2((untag(t[j].x) - m) * LOG2E); pe[j][1] = ex2((untag(t[j].y) - m) * LOG2E);
                pe[j][2] = ex2((untag(t[j].z) - m) * LOG2E); pe[j][3] = ex2((untag(t[j].w) - m) * LOG2E);
                l += (pe[j][0] + pe[j][1]) + (pe[j][2] + pe[j][3]);
            }
#pragma unroll
            for (int o = 16; o; o >>= 1) l += __shfl_xor_sync(0xffffffffu, l, o);
            if (lane == 0) s_misc[8 + warp] = l;
            __syncthreads();
            const float il = 1.f / sum8<1>(s_misc + 8);
#pragma unroll
            for (int j = 0; j < 4; j++) {
                const uint32_t p0 = (pack_bf(pe[j][0] * il, pe[j][1] * il) & 0x7fffffffu) | (tag << 31);
                const uint32_t p1 = (pack_bf(pe[j][2] * il, pe[j][3] * il) & 0x7fffffffu) | (tag << 31);
                asm volatile("st.relaxed.gpu.global.v2.u32 [%0], {%1,%2};"
                             :: "l"(&P.s[OFF_P + h * (WIN / 2) + (j * THREADS + tid) * 2]), "r"(p0), "r"(p1) : "memory");
            }
        }
        return;
    }

    const int c = tid & 7, g4 = lane >> 3;
    const int wr = tid >= 96;
    const int g = lane >> 2, t = lane & 3;
    const uint32_t s_warp = (uint32_t)__cvta_generic_to_shared(s_tile) + warp * 4096;
    const uint32_t sf = s_warp + g4 * 128 + ((c ^ g4) << 4);
    const uint32_t at_addr = s_warp + ((lane & 7) + ((lane >> 4) << 3)) * 128 + ((((lane >> 3) & 1) ^ (lane & 7)) << 4);
    float* red = s_red + warp * 64 + t * 16 + g;
    if (n == 65) {
        const int cbk = cl - C_F;
        const uint32_t t0 = now_ns() - cbk * T_CB, c0 = clock();
        cluster_arrive();
        const uint32_t off = (uint32_t)((k * OROWS + warp * 32 + g4) * (D_MODEL * 2) + cbk * 128 + c * 16);
#pragma unroll
        for (int i = 0; i < 16; i++) {
            wait_ns(t0, c0, T_LOAD + i * T_STEP);
            cp16(row_slot(sf, i & 7) + (i < 8 ? BLK2 : 0),
                 (i < 8 ? P.wd : P.wo + NOH * DH * (D_MODEL * 2)) + off + (i & 7) * 4 * (D_MODEL * 2));
            if (i == 7 || i == 11 || i == 15) asm volatile("cp.async.commit_group;" ::: "memory");
        }
        const uint32_t raddr = at_rank0(s_x + (k * 64 + (tid & 63)) * 4), rbar = at_rank0(xbar);
        float acc[4][4];
        bar_sync(3, THREADS);
        cluster_wait();
        {
            const uint32_t* wx = s_w + DH / 2 + warp * 16 + t;
#pragma unroll
            for (int i = 0; i < 4; i++) acc[i][0] = acc[i][1] = acc[i][2] = acc[i][3] = 0.f;
            asm volatile("cp.async.wait_group 2;" ::: "memory");
            __syncwarp();
            gemv16(acc, at_addr + BLK2, wx[0], wx[4]);
            gemv16(acc, at_addr + BLK2 + 2048, wx[8], wx[12]);
            store_sums(red + DATA_WARPS * 64, acc, t);
        }
        bar_sync(2, DATA_WARPS * 32);
        if (tid < 64) send(raddr + CL * 64 * 4, rbar + 8, sum6<64>(s_red + DATA_WARPS * 64 + tid));
        bar_sync(1, THREADS);
        uint32_t w[4];
#pragma unroll
        for (int j = 0; j < 4; j++) w[j] = s_w[warp * 16 + j * 4 + t];
#pragma unroll
        for (int i = 0; i < 4; i++) acc[i][0] = acc[i][1] = acc[i][2] = acc[i][3] = 0.f;
        asm volatile("cp.async.wait_group 1;" ::: "memory");
        __syncwarp();
        gemv16(acc, at_addr, w[0], w[1]);
        asm volatile("cp.async.wait_group 0;" ::: "memory");
        __syncwarp();
        gemv16(acc, at_addr + 2048, w[2], w[3]);
        store_sums(red, acc, t);
        bar_sync(2, DATA_WARPS * 32);
        if (tid < 64) send(raddr, rbar, sum6<64>(s_red + tid));
        return;
    }
    uint32_t* dst;
    if (n == 64) {
        const int rb = u / NCB, cbk = u - rb * NCB;
        spin_cycles(min(u * 10, OHOLD));
        load_rows<8, D_MODEL * 2>(sf, P.wo + (uint32_t)((rb * OROWS + warp * 32 + g4) * (D_MODEL * 2) + cbk * 128 + c * 16));
        dst = &P.s[OFF_FIN + (cbk * NOH + rb) * 64 + tid];
    } else if (n >= 0) {
        const bool isv = n >= NHEAD;
        const int h = n & (NHEAD - 1), r = (u & 7) * CL + k;
        load_rows<8, DH * 2>(sf, (isv ? P.v : P.k) + (size_t)h * (SK * DH * 2) +
                                 (uint32_t)((r * KROWS + wr * 32 + g4) * (DH * 2) + (warp - wr * 3) * 128 + c * 16));
        dst = isv ? &P.s[OFF_VP + (u - NHEAD * 8) * DH + tid] : &P.s[OFF_SC + h * WIN + r * KROWS + tid];
        if (isv) cluster_arrive();
    } else {
        dst = &P.s[OFF_F + cl * DH + tid];
        cluster_arrive();
    }
    bar_sync(1, THREADS);
    const uint32_t tag = s_tag;
    float acc[4][4];
#pragma unroll
    for (int i = 0; i < 4; i++) acc[i][0] = acc[i][1] = acc[i][2] = acc[i][3] = 0.f;

    if ((uint32_t)n < (uint32_t)NHEAD) {
        const int cb = warp - wr * 3;
        uint32_t q[8];
#pragma unroll
        for (int j = 0; j < 8; j++) q[j] = s_w[cb * 32 + j * 4 + t];
        const uint32_t a_addr = s_warp + (lane & 15) * 128 + (((lane >> 4) ^ (lane & 7)) << 4);
        asm volatile("cp.async.wait_all;" ::: "memory");
        __syncwarp();
#pragma unroll
        for (int ks = 0; ks < 4; ks++)
#pragma unroll
            for (int i = 0; i < 2; i++) {
                uint32_t a[4];
                ldsm4(a, (a_addr ^ (ks << 5)) + i * 2048);
                mma_bf16(acc[(ks & 1) * 2 + i], a, q[2 * ks], q[2 * ks + 1]);
            }
        s_red[cb * KROWS + wr * 32 + t * 8 + g] = (t & 2) ? ((t & 1) ? acc[1][2] + acc[3][2] : acc[1][0] + acc[3][0])
                                                          : ((t & 1) ? acc[0][2] + acc[2][2] : acc[0][0] + acc[2][0]);
        bar_sync(2, DATA_WARPS * 32);
        if (tid < KROWS) {
            const float v = s_red[tid] + s_red[KROWS + tid] + s_red[2 * KROWS + tid];
            st_tag(dst, rbf(rbf(v) * 0.07216878364870322f), tag);
        }
    } else {
        const bool wide = n < 64;
        const int w0 = (wide ? wr : warp) * 16 + t;
        uint32_t w[4];
#pragma unroll
        for (int j = 0; j < 4; j++) w[j] = s_w[w0 + j * 4];
        if (wide) cluster_wait();
        asm volatile("cp.async.wait_all;" ::: "memory");
        __syncwarp();
        gemv16(acc, at_addr, w[0], w[1]);
        gemv16(acc, at_addr + 2048, w[2], w[3]);
        if (n < 0 && !wr) gemv16(acc, at_addr + BLK2, s_w[32 + t], s_w[36 + t]);
        store_sums(red, acc, t);
        bar_sync(2, DATA_WARPS * 32);
        if (wide) {
            send(at_rank0(s_x + (k * DH + tid) * 4), at_rank0(xbar), s_red[tid] + s_red[DH + tid]);
            if (k == 0) {
                xbar_wait(xbar);
                const float v = sum8<DH>(xch + tid);
                st_tag(dst, n < 0 ? rbf(v) : v, tag);
            }
        } else if (tid < 64) {
            st_tag(dst, sum6<64>(s_red + tid), tag);
        }
    }
}

}

extern "C" void kernel_launch(void* const* d_in, const int* in_sizes, int n_in, void* d_out, int out_size) {
    (void)in_sizes; (void)n_in; (void)out_size;
    Params P;
    P.x      = (const char*)d_in[0];
    P.k      = (const char*)d_in[1] + (size_t)(SK - WIN) * DH * 2;
    P.v      = (const char*)d_in[2] + (size_t)(SK - WIN) * DH * 2;
    P.wq     = (const char*)d_in[3];
    P.wo     = (const char*)d_in[4];
    P.wg     = (const char*)d_in[6];
    P.wu     = (const char*)d_in[7];
    P.wd     = (const char*)d_in[8];
    P.gate_w = (const char*)d_in[9];
    P.out    = (__nv_bfloat16*)d_out;
    void* scratch = nullptr;
    cudaGetSymbolAddress(&scratch, g_scratch);
    P.s      = (uint32_t*)scratch;
    cudaFuncSetAttribute(fused_decode_kernel, cudaFuncAttributeMaxDynamicSharedMemorySize, DYN_SMEM);
    fused_decode_kernel<<<GRID, THREADS, DYN_SMEM, cudaStreamPerThread>>>(P);
}
```
